```python
import torch

def _softmax(x, axis=-1):
    return torch.softmax(x, dim=axis)
def _gelu(x):
    return torch.nn.functional.gelu(x, approximate="tanh")
def _silu(x):
    return torch.nn.functional.silu(x)
def _sigmoid(x):
    return torch.sigmoid(x)
def _layernorm(x, axis=-1, eps=1e-5):
    m = x.mean(dim=axis, keepdim=True)
    v = x.var(dim=axis, keepdim=True, unbiased=False)
    return (x - m) / torch.sqrt(v + eps)
def _scatter_add(tgt, idx, src, axis=0):
    return tgt.clone().index_add_(axis, idx, src)
def _segment_sum(src, seg, n):
    out = torch.zeros((n,) + src.shape[1:], dtype=src.dtype)
    return out.index_add_(0, seg, src)
def _pad(x, pw):
    flat = tuple(v for pair in reversed(pw) for v in pair)
    return torch.nn.functional.pad(x, flat)

kernel_name = 'standalone__gated_linear_recurrence__prompt'

def setup_inputs():

    _w = (lambda a: (lambda t: t.to(torch.bfloat16) if t.is_floating_point() else t)(torch.as_tensor(a)))
    B, H, T, D = 1, 16, 2048, 256
    return {
        "q": _w((lambda *s: torch.randn(*s, dtype=torch.bfloat16) * 0.05)(B, H, T, D)),
        "k": _w((lambda *s: torch.randn(*s, dtype=torch.bfloat16) * 0.05)(B, H, T, D)),
        "v": _w((lambda *s: torch.randn(*s, dtype=torch.bfloat16) * 0.05)(B, H, T, D)),
        "g": _w((lambda *s: torch.randn(*s, dtype=torch.bfloat16) * 0.8)(B, H, T, D)),
    }

def reference(q, k, v, g):
    B, H, T, D = q.shape
    scale = D ** -0.5
    a = _sigmoid(g)
    S = k[:, :, 0, :, None] * v[:, :, 0, None, :] * 0.0
    outs = []
    for t in range(T):
        S = a[:, :, t, :, None] * S + k[:, :, t, :, None] * v[:, :, t, None, :]
        ot = torch.einsum("bhd,bhde->bhe", q[:, :, t, :], S) * scale
        outs.append(ot)
    return torch.stack(outs, 2)
```

```cpp
#include <cuda_runtime.h>
#include <cuda_bf16.h>
#include <cuda.h>
#include <stdint.h>

namespace gla {

constexpr int H = 16, T = 2048, D = 256, C = 64, NCHUNK = T / C;

#define SEG0 8
#define SEG1 8
#define SEG2 8

constexpr uint32_t TILE = 8192;
constexpr uint32_t QKG_BYTES = 6 * TILE;
constexpr uint32_t V_BYTES = 4 * TILE;
constexpr int NQ = 3;
constexpr uint32_t OFF_QKG = 0;
constexpr uint32_t OFF_V = OFF_QKG + NQ * QKG_BYTES;
constexpr uint32_t OFF_RECV = OFF_V + 2 * V_BYTES;
constexpr uint32_t EVEC = 576;
constexpr uint32_t E_OFF = 5 * TILE;
constexpr uint32_t OFF_CARRY = OFF_RECV + 2 * TILE;
constexpr uint32_t OFF_AUXD = OFF_CARRY + 1024;
constexpr uint32_t OFF_AUXC = OFF_AUXD + EVEC;
constexpr uint32_t OFF_BAR = OFF_AUXC + EVEC;
constexpr uint32_t BAR_RAW = OFF_BAR;
constexpr uint32_t BAR_READY = BAR_RAW + 8 * NQ;
constexpr uint32_t BAR_V = BAR_READY + 8 * NQ;
constexpr uint32_t BAR_RECV = BAR_V + 16;
constexpr uint32_t BAR_SENDOK = BAR_RECV + 16;
constexpr uint32_t OFF_CNT = BAR_SENDOK + 16;
constexpr uint32_t SMEM_BYTES = OFF_CNT + 8;
static_assert(SMEM_BYTES <= 232448, "smem");

constexpr float SAFE_LIMIT = 4.611686018427388e18f;
constexpr float NLOG2E = -1.4426950408889634f;

__device__ uint4 g_state[H * 2 * 2 * 8 * 16 * 32];
__device__ unsigned int g_flag[H * 2 * 2 * 8];

#define TRACE(role, n, ev)
__device__ __forceinline__ uint32_t smem_u32(const void* p) { return (uint32_t)__cvta_generic_to_shared(p); }

__device__ __forceinline__ void mbar_init(uint32_t bar, uint32_t count) {
  asm volatile("mbarrier.init.shared::cta.b64 [%0], %1;" ::"r"(bar), "r"(count) : "memory");
}
__device__ __forceinline__ void mbar_expect_tx(uint32_t bar, uint32_t bytes) {
  asm volatile("mbarrier.arrive.expect_tx.shared::cta.b64 _, [%0], %1;" ::"r"(bar), "r"(bytes) : "memory");
}
__device__ __forceinline__ void mbar_arrive(uint32_t bar) {
  asm volatile("mbarrier.arrive.shared::cta.b64 _, [%0];" ::"r"(bar) : "memory");
}
__device__ __forceinline__ void mbar_arrive_remote(uint32_t remote_bar) {
  asm volatile("mbarrier.arrive.relaxed.cluster.shared::cluster.b64 _, [%0];" ::"r"(remote_bar) : "memory");
}
__device__ __forceinline__ void mbar_wait(uint32_t bar, uint32_t parity) {
  asm volatile(
      "{\n.reg .pred p;\n.reg .u32 n;\nmov.u32 n, 0;\n"
      "WAIT_LOOP:\n"
      "mbarrier.try_wait.parity.shared::cta.b64 p, [%0], %1;\n"
      "@p bra WAIT_DONE;\n"
      "add.u32 n, n, 1;\nsetp.gt.u32 p, n, 4000000;\n@p trap;\n"
      "bra WAIT_LOOP;\n"
      "WAIT_DONE:\n}\n" ::"r"(bar), "r"(parity) : "memory");
}
__device__ __forceinline__ void flag_wait(const unsigned int* flag) {
  asm volatile(
      "{\n.reg .pred p;\n.reg .u32 n, f;\nmov.u32 n, 0;\n"
      "WAIT_LOOP:\n"
      "ld.relaxed.gpu.global.u32 f, [%0];\n"
      "setp.ne.u32 p, f, 0;\n"
      "@p bra WAIT_DONE;\n"
      "add.u32 n, n, 1;\nsetp.gt.u32 p, n, 4000000;\n@p trap;\n"
      "bra WAIT_LOOP;\n"
      "WAIT_DONE:\nfence.acq_rel.gpu;\n}\n" ::"l"(flag) : "memory");
}
__device__ __forceinline__ uint32_t mapa(uint32_t addr, uint32_t rank) {
  uint32_t r;
  asm("mapa.shared::cluster.u32 %0, %1, %2;" : "=r"(r) : "r"(addr), "r"(rank));
  return r;
}
__device__ __forceinline__ bool elect_one() {
  uint32_t r;
  asm volatile("{\n.reg .pred p;\nelect.sync _|p, 0xffffffff;\nselp.u32 %0, 1, 0, p;\n}\n" : "=r"(r));
  return r != 0;
}
__device__ __forceinline__ uint32_t uniform(uint32_t v) { return __shfl_sync(0xffffffffu, v, 0); }
__device__ __forceinline__ void fence_proxy_async() { asm volatile("fence.proxy.async.shared::cta;" ::: "memory"); }
template <int ID> __device__ __forceinline__ void bar_sync128() { asm volatile("bar.sync %0, 128;" ::"n"(ID) : "memory"); }
template <int ID> __device__ __forceinline__ bool bar_red_or128(bool v) {
  uint32_t r;
  asm volatile(
      "{\n.reg .pred p, q;\nsetp.ne.u32 q, %2, 0;\n"
      "bar.red.or.pred p, %1, 128, q;\nselp.u32 %0, 1, 0, p;\n}\n"
      : "=r"(r) : "n"(ID), "r"((uint32_t)v) : "memory");
  return r != 0;
}
__device__ __forceinline__ void tma_load(uint32_t dst, const CUtensorMap* map, int row, int blk, uint32_t bar) {
  asm volatile(
      "cp.async.bulk.tensor.3d.shared::cluster.global.mbarrier::complete_tx::bytes [%0], [%1, {0, %3, %4}], [%2];"
      ::"r"(dst), "l"((uint64_t)map), "r"(bar), "r"(row), "r"(blk) : "memory");
}
__device__ __forceinline__ void tma_store(const CUtensorMap* map, int row, int blk, uint32_t src) {
  asm volatile("cp.async.bulk.tensor.3d.global.shared::cta.bulk_group [%0, {0, %2, %3}], [%1];"
               ::"l"((uint64_t)map), "r"(src), "r"(row), "r"(blk) : "memory");
}
__device__ __forceinline__ void bulk_commit() { asm volatile("cp.async.bulk.commit_group;" ::: "memory"); }
__device__ __forceinline__ void bulk_wait_read0() { asm volatile("cp.async.bulk.wait_group.read 0;" ::: "memory"); }
__device__ __forceinline__ void bulk_wait0() { asm volatile("cp.async.bulk.wait_group 0;" ::: "memory"); }

__device__ __forceinline__ uint32_t lds32(uint32_t a) {
  uint32_t v;
  asm volatile("ld.shared.b32 %0, [%1];" : "=r"(v) : "r"(a));
  return v;
}
__device__ __forceinline__ void sts32(uint32_t a, uint32_t v) { asm volatile("st.shared.b32 [%0], %1;" ::"r"(a), "r"(v)); }
__device__ __forceinline__ void sts16(uint32_t a, uint16_t v) { asm volatile("st.shared.b16 [%0], %1;" ::"r"(a), "h"(v)); }
__device__ __forceinline__ void sts_f2(uint32_t a, float x, float y) {
  asm volatile("st.shared.v2.f32 [%0], {%1, %2};" ::"r"(a), "f"(x), "f"(y));
}
__device__ __forceinline__ float2 lds_f2(uint32_t a) {
  float2 v;
  asm volatile("ld.shared.v2.f32 {%0, %1}, [%2];" : "=f"(v.x), "=f"(v.y) : "r"(a));
  return v;
}
__device__ __forceinline__ float4 lds_f4(uint32_t a) {
  float4 v;
  asm volatile("ld.shared.v4.f32 {%0, %1, %2, %3}, [%4];" : "=f"(v.x), "=f"(v.y), "=f"(v.z), "=f"(v.w) : "r"(a));
  return v;
}
__device__ __forceinline__ uint4 lds_u4(uint32_t a) {
  uint4 v;
  asm volatile("ld.shared.v4.b32 {%0, %1, %2, %3}, [%4];" : "=r"(v.x), "=r"(v.y), "=r"(v.z), "=r"(v.w) : "r"(a));
  return v;
}
__device__ __forceinline__ void st_async_v4(uint32_t remote_addr, uint32_t a, uint32_t b, uint32_t c, uint32_t d,
                                            uint32_t remote_bar) {
  asm volatile("st.async.weak.shared::cluster.mbarrier::complete_tx::bytes.v4.b32 [%0], {%1, %2, %3, %4}, [%5];"
               ::"r"(remote_addr), "r"(a), "r"(b), "r"(c), "r"(d), "r"(remote_bar) : "memory");
}
__device__ __forceinline__ void stmatrix_x4(uint32_t a, uint32_t r0, uint32_t r1, uint32_t r2, uint32_t r3) {
  asm volatile("stmatrix.sync.aligned.m8n8.x4.shared.b16 [%0], {%1, %2, %3, %4};"
               ::"r"(a), "r"(r0), "r"(r1), "r"(r2), "r"(r3) : "memory");
}
__device__ __forceinline__ void stmatrix_x4_trans(uint32_t a, uint32_t r0, uint32_t r1, uint32_t r2, uint32_t r3) {
  asm volatile("stmatrix.sync.aligned.m8n8.x4.trans.shared.b16 [%0], {%1, %2, %3, %4};"
               ::"r"(a), "r"(r0), "r"(r1), "r"(r2), "r"(r3) : "memory");
}
__device__ __forceinline__ float ex2f(float x) { float y; asm("ex2.approx.ftz.f32 %0, %1;" : "=f"(y) : "f"(x)); return y; }
__device__ __forceinline__ float rcpf(float x) { float y; asm("rcp.approx.ftz.f32 %0, %1;" : "=f"(y) : "f"(x)); return y; }
__device__ __forceinline__ uint32_t pack_bf16(float lo, float hi) {
  uint32_t r;
  asm("cvt.rn.bf16x2.f32 %0, %1, %2;" : "=r"(r) : "f"(hi), "f"(lo));
  return r;
}
__device__ __forceinline__ uint32_t mul_bf16x2(uint32_t a, uint32_t b) {
  uint32_t r;
  asm("mul.rn.bf16x2 %0, %1, %2;" : "=r"(r) : "r"(a), "r"(b));
  return r;
}
__device__ __forceinline__ uint32_t add_bf16x2(uint32_t a, uint32_t b) {
  uint32_t r;
  asm("add.rn.bf16x2 %0, %1, %2;" : "=r"(r) : "r"(a), "r"(b));
  return r;
}
__device__ __forceinline__ uint16_t lds16(uint32_t a) {
  uint16_t v;
  asm volatile("ld.shared.b16 %0, [%1];" : "=h"(v) : "r"(a));
  return v;
}
__device__ __forceinline__ float bf_lo(uint32_t w) { return __uint_as_float(w << 16); }
__device__ __forceinline__ float bf_hi(uint32_t w) { return __uint_as_float(w & 0xffff0000u); }

__device__ __forceinline__ void wg_fence() { asm volatile("wgmma.fence.sync.aligned;" ::: "memory"); }
__device__ __forceinline__ void wg_commit() { asm volatile("wgmma.commit_group.sync.aligned;" ::: "memory"); }
template <int N> __device__ __forceinline__ void wg_wait() {
  asm volatile("wgmma.wait_group.sync.aligned %0;" ::"n"(N) : "memory");
}
template <int N> __device__ __forceinline__ void reg_fence(float (&r)[N]) {
#pragma unroll
  for (int i = 0; i < N; i++) asm volatile("" : "+f"(r[i])::"memory");
}
template <int N> __device__ __forceinline__ void reg_fence(uint32_t (&r)[N]) {
#pragma unroll
  for (int i = 0; i < N; i++) asm volatile("" : "+r"(r[i])::"memory");
}
__device__ __forceinline__ uint32_t desc_k(uint32_t addr) { return ((addr & 0x3FFFF) >> 4) | (1u << 16); }
__device__ __forceinline__ uint32_t desc_mn(uint32_t addr) { return ((addr & 0x3FFFF) >> 4) | ((TILE >> 4) << 16); }
#define DESC_HI "0x40000040"

#define ACC8(d, o) "+f"(d[o + 0]), "+f"(d[o + 1]), "+f"(d[o + 2]), "+f"(d[o + 3]), "+f"(d[o + 4]), "+f"(d[o + 5]), "+f"(d[o + 6]), "+f"(d[o + 7])
#define ACC32(d) ACC8(d, 0), ACC8(d, 8), ACC8(d, 16), ACC8(d, 24)
#define ACC64(d) ACC32(d), ACC8(d, 32), ACC8(d, 40), ACC8(d, 48), ACC8(d, 56)
#define REGS32 "{%0,%1,%2,%3,%4,%5,%6,%7,%8,%9,%10,%11,%12,%13,%14,%15,%16,%17,%18,%19,%20,%21,%22,%23,%24,%25,%26,%27,%28,%29,%30,%31}"
#define REGS64 "{%0,%1,%2,%3,%4,%5,%6,%7,%8,%9,%10,%11,%12,%13,%14,%15,%16,%17,%18,%19,%20,%21,%22,%23,%24,%25,%26,%27,%28,%29,%30,%31," \
               "%32,%33,%34,%35,%36,%37,%38,%39,%40,%41,%42,%43,%44,%45,%46,%47,%48,%49,%50,%51,%52,%53,%54,%55,%56,%57,%58,%59,%60,%61,%62,%63}"

template <int ACC>
__device__ __forceinline__ void wgmma_n64_rs(float (&d)[32], uint32_t a0, uint32_t a1, uint32_t a2, uint32_t a3,
                                             uint32_t bdesc) {
  asm volatile(
      "{\n.reg .b64 db;\nmov.b64 db, {%36, " DESC_HI "};\n"
      "wgmma.mma_async.sync.aligned.m64n64k16.f32.bf16.bf16 " REGS32 ", {%32,%33,%34,%35}, db, %37, 1, 1, 0;\n}\n"
      : ACC32(d) : "r"(a0), "r"(a1), "r"(a2), "r"(a3), "r"(bdesc), "n"(ACC));
}
template <int TA, int ACC>
__device__ __forceinline__ void wgmma_n64_ss(float (&d)[32], uint32_t adesc, uint32_t bdesc) {
  asm volatile(
      "{\n.reg .b64 da, db;\nmov.b64 da, {%32, " DESC_HI "};\nmov.b64 db, {%33, " DESC_HI "};\n"
      "wgmma.mma_async.sync.aligned.m64n64k16.f32.bf16.bf16 " REGS32 ", da, db, %34, 1, 1, %35, 0;\n}\n"
      : ACC32(d) : "r"(adesc), "r"(bdesc), "n"(ACC), "n"(TA));
}
__device__ __forceinline__ void wgmma_n128_tt(float (&d)[64], uint32_t adesc, uint32_t bdesc) {
  asm volatile(
      "{\n.reg .b64 da, db;\nmov.b64 da, {%64, " DESC_HI "};\nmov.b64 db, {%65, " DESC_HI "};\n"
      "wgmma.mma_async.sync.aligned.m64n128k16.f32.bf16.bf16 " REGS64 ", da, db, 1, 1, 1, 1, 1;\n}\n"
      : ACC64(d) : "r"(adesc), "r"(bdesc));
}

struct Maps { CUtensorMap q, k, g, v, o; };

__device__ __forceinline__ void load_qkg(uint32_t sb, const Maps& m, int stage, int row, int rank, bool main_mode) {
  const uint32_t qkg = sb + OFF_QKG + stage * QKG_BYTES, bar = sb + BAR_RAW + stage * 8;
  mbar_expect_tx(bar, main_mode ? 6 * TILE : 4 * TILE);
  tma_load(qkg + 4 * TILE, &m.g, row, rank * 2, bar);
  tma_load(qkg + 2 * TILE, &m.k, row, rank * 2, bar);
  if (main_mode) tma_load(qkg, &m.q, row, rank * 2, bar);
}
__device__ __forceinline__ void load_v(uint32_t sb, const Maps& m, int stage, int row) {
  const uint32_t bar = sb + BAR_V + stage * 8;
  mbar_expect_tx(bar, V_BYTES);
  tma_load(sb + OFF_V + stage * V_BYTES, &m.v, row, 0, bar);
}

__device__ __forceinline__ void scale_state(float (&S)[64], uint32_t eaddr) {
#pragma unroll
  for (int i = 0; i < 8; i++) {
    float4 e = lds_f4(eaddr + i * 16);
    S[8 * i + 0] *= e.x; S[8 * i + 1] *= e.y; S[8 * i + 2] *= e.x; S[8 * i + 3] *= e.y;
    S[8 * i + 4] *= e.z; S[8 * i + 5] *= e.w; S[8 * i + 6] *= e.z; S[8 * i + 7] *= e.w;
  }
}
template <int HALF>
__device__ __forceinline__ void cvt_state(uint32_t (&Af)[16], const float (&S)[64]) {
#pragma unroll
  for (int i = 0; i < 16; i++) Af[i] = pack_bf16(S[HALF * 32 + 2 * i], S[HALF * 32 + 2 * i + 1]);
}

template <bool MAIN, bool UPPER>
__device__ __forceinline__ bool prep_half(uint32_t qa, float& f0, float& f1) {
  constexpr float INIT = (MAIN && !UPPER) ? 0.0625f : 1.f;
  float p0 = INIT, p1 = INIT, r0 = 1.f, r1 = 1.f;
  uint32_t rb = qa + (UPPER ? 32 : 24) * 128;
  uint32_t gw[8];
#pragma unroll
  for (int i = 0; i < 8; i++) {
    const int r = UPPER ? i : 7 - i;
    gw[i] = lds32((rb ^ (r << 4)) + r * 128 + 4 * TILE);
  }
#pragma unroll 1
  for (int b8 = 0; b8 < 4; b8++) {
    uint32_t kw[8], qw[8];
    float e0[8], e1[8];
#pragma unroll
    for (int i = 0; i < 8; i++) {
      const int r = UPPER ? i : 7 - i;
      const uint32_t a = (rb ^ (r << 4)) + r * 128;
      kw[i] = lds32(a + 2 * TILE);
      if (MAIN) qw[i] = lds32(a);
      e0[i] = ex2f(bf_lo(gw[i]) * NLOG2E);
      e1[i] = ex2f(bf_hi(gw[i]) * NLOG2E);
      gw[i] = lds32(a + 4 * TILE + (b8 == 3 ? 0 : (UPPER ? 1024 : -1024)));
    }
    if (UPPER) {
#pragma unroll
      for (int i = 0; i < 8; i++) {
        p0 = fmaf(p0, e0[i], p0); p1 = fmaf(p1, e1[i], p1);
        sts32((rb ^ (i << 4)) + i * 128 + 2 * TILE, mul_bf16x2(kw[i], pack_bf16(p0, p1)));
      }
      if (MAIN) {
        r0 = rcpf(p0) * 0.0625f; r1 = rcpf(p1) * 0.0625f;
#pragma unroll
        for (int i = 7; i >= 0; i--) {
          sts32((rb ^ (i << 4)) + i * 128, mul_bf16x2(qw[i], pack_bf16(r0, r1)));
          r0 = fmaf(r0, e0[i], r0); r1 = fmaf(r1, e1[i], r1);
        }
      }
      rb += 1024;
    } else {
#pragma unroll
      for (int i = 0; i < 8; i++) {
        if (MAIN) sts32((rb ^ ((7 - i) << 4)) + (7 - i) * 128, mul_bf16x2(qw[i], pack_bf16(p0, p1)));
        p0 = fmaf(p0, e0[i], p0); p1 = fmaf(p1, e1[i], p1);
      }
      r0 = rcpf(p0) * INIT; r1 = rcpf(p1) * INIT;
      f0 = r0; f1 = r1;
#pragma unroll
      for (int i = 7; i >= 0; i--) {
        r0 = fmaf(r0, e0[i], r0); r1 = fmaf(r1, e1[i], r1);
        sts32((rb ^ ((7 - i) << 4)) + (7 - i) * 128 + 2 * TILE, mul_bf16x2(kw[i], pack_bf16(r0, r1)));
      }
      rb -= 1024;
    }
  }
  if (UPPER) { f0 = rcpf(p0); f1 = rcpf(p1); }
  return p0 <= SAFE_LIMIT * INIT && p1 <= SAFE_LIMIT * INIT;
}

__device__ __forceinline__ float sigmoid_f(float g) { return rcpf(1.f + ex2f(g * NLOG2E)); }

__device__ __forceinline__ void gemm_qk(float (&acc)[32], uint32_t dq) {
  const uint32_t dk = dq + ((2 * TILE) >> 4);
  wg_fence();
  wgmma_n64_ss<0, 0>(acc, dq, dk);
#pragma unroll
  for (int kk = 1; kk < 8; kk++) {
    const uint32_t off = ((kk >> 2) * TILE + (kk & 3) * 32) >> 4;
    wgmma_n64_ss<0, 1>(acc, dq + off, dk + off);
  }
  wg_commit();
  wg_wait<0>();
  reg_fence(acc);
}
template <int HALF>
__device__ __forceinline__ void gemm_inter(float (&O)[32], const uint32_t (&Af)[16], uint32_t dq) {
  dq += (HALF * TILE) >> 4;
  wgmma_n64_rs<HALF>(O, Af[0], Af[1], Af[2], Af[3], dq);
#pragma unroll
  for (int kk = 1; kk < 4; kk++) wgmma_n64_rs<1>(O, Af[4 * kk], Af[4 * kk + 1], Af[4 * kk + 2], Af[4 * kk + 3], dq + kk * 2);
}
__device__ __forceinline__ void gemm_intra(float (&O)[32], uint32_t dq, uint32_t dv) {
  const uint32_t da = dq + ((4 * TILE) >> 4);
#pragma unroll
  for (int ks = 0; ks < 4; ks++) wgmma_n64_ss<1, 1>(O, dv + ks * 128, da + ks * 2);
}
__device__ __forceinline__ void gemm_state(float (&S)[64], uint32_t dq, uint32_t dv) {
  const uint32_t dk = dq + ((2 * TILE) >> 4) + (((TILE >> 4) - 1) << 16);
#pragma unroll
  for (int ks = 0; ks < 4; ks++) wgmma_n128_tt(S, dv + ks * 128, dk + ks * 128);
}

__global__ void __cluster_dims__(2, 1, 1) __launch_bounds__(384, 1)
gla_kernel(const __grid_constant__ Maps maps, const uint32_t* __restrict__ gq, const uint32_t* __restrict__ gk,
           const uint32_t* __restrict__ gg) {
  extern __shared__ __align__(1024) uint8_t smem_raw[];
  const uint32_t sb = smem_u32(smem_raw);
  const int tid = threadIdx.x, lane = tid & 31;
  const int warp = __shfl_sync(0xffffffffu, tid >> 5, 0), wg = warp >> 2;
  uint32_t rank;
  asm("mov.u32 %0, %%cluster_ctarank;" : "=r"(rank));
  const int cid = blockIdx.x >> 1;
  const int head = cid >> 2, seg = cid & 3;
  const int b1 = SEG0, b2 = SEG0 + SEG1, b3 = SEG0 + SEG1 + SEG2;
  const int c_begin = seg <= 1 ? 0 : (seg == 2 ? b1 : b2);
  const int c_main = seg == 0 ? 0 : (seg == 1 ? b1 : (seg == 2 ? b2 : b3));
  const int c_end = seg == 0 ? b1 : (seg == 1 ? b2 : (seg == 2 ? b3 : NCHUNK));
  const int row0 = head * T;

  TRACE(wg, 39, 0);
  if (warp == 0) {
    if (elect_one()) {
#pragma unroll
      for (int s = 0; s < NQ; s++) {
        mbar_init(sb + BAR_RAW + s * 8, 1);
        mbar_init(sb + BAR_READY + s * 8, 128);
      }
#pragma unroll
      for (int s = 0; s < 2; s++) {
        mbar_init(sb + BAR_V + s * 8, 1);
        mbar_init(sb + BAR_RECV + s * 8, 1);
        mbar_init(sb + BAR_SENDOK + s * 8, 1);
        sts32(sb + OFF_CNT + s * 4, 0);
      }
      asm volatile("fence.mbarrier_init.release.cluster;" ::: "memory");
      if (sb & 1023u) asm volatile("trap;");
      load_qkg(sb, maps, 0, row0 + c_begin * C, rank, c_begin >= c_main);
      load_v(sb, maps, 0, row0 + c_begin * C);
      load_qkg(sb, maps, 1, row0 + (c_begin + 1) * C, rank, c_begin + 1 >= c_main);
      load_v(sb, maps, 1, row0 + (c_begin + 1) * C);
      load_qkg(sb, maps, 2, row0 + (c_begin + 2) * C, rank, c_begin + 2 >= c_main);
    }
  }
  __syncthreads();
  asm volatile("barrier.cluster.arrive.relaxed.aligned;" ::: "memory");

  if (wg == 2) {
    asm volatile("setmaxnreg.dec.sync.aligned.u32 72;");
    const int pw = warp - 8, blk = pw & 1, half = pw >> 1;
    const int cp = blk * 32 + lane;
    const uint32_t lane_off = blk * TILE + lane * 4;
    const uint32_t eoff = ((cp & 3) * 36 + (cp >> 2) * 2) * 4;
    float dt0 = 1.f, dt1 = 1.f;
    if (half) sts_f2(sb + OFF_CARRY + 512 + cp * 8, 1.f, 1.f);
    bar_sync128<1>();
    int sq = 0;
    uint32_t pq = 0;
#pragma unroll 1
    for (int c = c_begin; c < c_end; c++) {
      const int n = c - c_begin;
      const bool main_mode = c >= c_main;
      const uint32_t qkg = sb + OFF_QKG + sq * QKG_BYTES;
      const uint32_t carry_prev = sb + OFF_CARRY + ((n & 1) ^ 1) * 512 + cp * 8;
      const uint32_t carry_cur = sb + OFF_CARRY + (n & 1) * 512 + cp * 8;
      TRACE(2, n, 0);
      mbar_wait(sb + BAR_RAW + sq * 8, pq);
      TRACE(2, n, 1);
      float f0, f1;
      bool safe;
      if (main_mode) {
        if (half) safe = prep_half<true, true>(qkg + lane_off, f0, f1); else safe = prep_half<true, false>(qkg + lane_off, f0, f1);
      } else {
        if (half) safe = prep_half<false, true>(qkg + lane_off, f0, f1); else safe = prep_half<false, false>(qkg + lane_off, f0, f1);
      }
      TRACE(2, n, 2);
      if (half) sts_f2(carry_cur, f0, f1);
      fence_proxy_async();
      const bool slow = uniform(bar_red_or128<4>(!safe)) != 0;
      TRACE(2, n, 3);
      if (!slow) {
        if (!half) {
          const float2 cprev = lds_f2(carry_prev);
          f0 *= cprev.x; f1 *= cprev.y;
          sts_f2(qkg + E_OFF + eoff, f0, f1);
          dt0 *= f0; dt1 *= f1;
        }
        if (main_mode) {
          float acc[32];
          gemm_qk(acc, uniform(desc_k(qkg)));
          int d = pw * 16 + (lane >> 2) - 2 * (lane & 3);
          asm volatile("" : "+r"(d));
          const uint32_t abase = qkg + 4 * TILE + (pw * 16 + (lane & 15)) * 128;
#pragma unroll
          for (int j = 0; j < 8; j += 2) {
            uint32_t r[4];
#pragma unroll
            for (int u = 0; u < 2; u++) {
              const int sc = 8 * (j + u);
              const float* a = &acc[4 * (j + u)];
              r[2 * u + 0] = pack_bf16(sc <= d ? a[0] : 0.f, sc + 1 <= d ? a[1] : 0.f);
              r[2 * u + 1] = pack_bf16(sc - 8 <= d ? a[2] : 0.f, sc - 7 <= d ? a[3] : 0.f);
            }
            stmatrix_x4(abase + (((j + (lane >> 4)) ^ (lane & 7)) << 4), r[0], r[1], r[2], r[3]);
          }
          fence_proxy_async();
        }
      } else {
        const size_t gbase = ((size_t)(row0 + c * C) * D + rank * 128) / 2 + cp;
        const int tb = half * 32;
        const uint32_t la = qkg + lane_off;
        float o0 = 1.f, o1 = 1.f, w0, w1;
#pragma unroll 1
        for (int lev = main_mode ? -1 : 6; lev < 7; lev++) {
          const int bm = lev < 0 ? 0 : (1 << lev) - 1;
          if (lev == 6) {
#pragma unroll 1
            for (int i = 0; i < 32; i++) {
              const uint32_t gw = gg[gbase + (size_t)((32 - tb) + i) * 128];
              o0 *= sigmoid_f(bf_lo(gw)); o1 *= sigmoid_f(bf_hi(gw));
            }
          }
          w0 = o0; w1 = o1;
          if (main_mode) {
#pragma unroll 1
            for (int i = 0; i < 32; i++) {
              const int t = tb + i;
              const uint32_t gw = gg[gbase + (size_t)t * 128], qw = gq[gbase + (size_t)t * 128];
              if ((t & bm) == 0) { w0 = 1.f; w1 = 1.f; }
              if (lev >= 0) { w0 *= sigmoid_f(bf_lo(gw)); w1 *= sigmoid_f(bf_hi(gw)); }
              sts32((la ^ ((t & 7) << 4)) + t * 128, pack_bf16(bf_lo(qw) * w0 * 0.0625f, bf_hi(qw) * w1 * 0.0625f));
            }
          }
          w0 = o0; w1 = o1;
#pragma unroll 1
          for (int i = 31; i >= 0; i--) {
            const int t = tb + i;
            const uint32_t gw = gg[gbase + (size_t)t * 128], kw = gk[gbase + (size_t)t * 128];
            if ((t & bm) == bm) { w0 = 1.f; w1 = 1.f; }
            sts32((la ^ ((t & 7) << 4)) + t * 128 + 2 * TILE, pack_bf16(bf_lo(kw) * w0, bf_hi(kw) * w1));
            w0 *= sigmoid_f(bf_lo(gw)); w1 *= sigmoid_f(bf_hi(gw));
          }
          if (lev < 6) {
            fence_proxy_async();
            bar_sync128<1>();
            float acc[32];
            gemm_qk(acc, uniform(desc_k(qkg)));
            const uint32_t tbase = qkg + 5 * TILE + (pw * 16 + (lane & 15)) * 128;
#pragma unroll
            for (int j = 0; j < 8; j += 2)
              stmatrix_x4(tbase + (((j + (lane >> 4)) ^ (lane & 7)) << 4), pack_bf16(acc[4 * j], acc[4 * j + 1]),
                          pack_bf16(acc[4 * j + 2], acc[4 * j + 3]), pack_bf16(acc[4 * j + 4], acc[4 * j + 5]),
                          pack_bf16(acc[4 * j + 6], acc[4 * j + 7]));
            __syncwarp();
#pragma unroll 1
            for (int i = 0; i < 32; i++) {
              const int t = pw * 16 + (i >> 1), sc = (i & 1) * 32 + lane;
              const uint32_t off = t * 128 + (((sc >> 3) ^ (t & 7)) << 4) + (sc & 7) * 2;
              const bool mine = lev < 0 ? (sc >= t) : (sc < t && ((t ^ sc) >> lev) == 1);
              const uint16_t val = sc > t ? (uint16_t)0 : lds16(qkg + 5 * TILE + off);
              if (mine) sts16(qkg + 4 * TILE + off, val);
            }
            bar_sync128<1>();
          }
        }
        if (half) {
          f0 = 1.f; f1 = 1.f;
          sts_f2(carry_cur, 1.f, 1.f);
        } else {
          const float2 cprev = lds_f2(carry_prev);
          sts_f2(qkg + E_OFF + eoff, cprev.x, cprev.y);
          sts_f2(qkg + E_OFF + EVEC + eoff, w0, w1);
          dt0 *= cprev.x * w0; dt1 *= cprev.y * w1;
        }
        fence_proxy_async();
        bar_sync128<1>();
      }
      if (c == c_main - 1) {
        if (half) sts_f2(sb + OFF_AUXC + eoff, f0, f1); else sts_f2(sb + OFF_AUXD + eoff, dt0, dt1);
      }
      if (tid == 256) sts32(qkg + E_OFF + 2 * EVEC, slow ? 1u : 0u);
      mbar_arrive(sb + BAR_READY + sq * 8);
      TRACE(2, n, 4);
      if (++sq == NQ) { sq = 0; pq ^= 1; }
    }
  } else {
    asm volatile("setmaxnreg.inc.sync.aligned.u32 216;");
    const int w4 = warp & 3;
    const int mbS = 2 * wg + (1 - rank), mbK = 2 * wg + rank;
    const uint32_t eq = (lane & 3) * 144;
    float S0[64], S1[64];
#pragma unroll
    for (int i = 0; i < 64; i++) { S0[i] = 0.f; S1[i] = 0.f; }
    int sq = 0;
    uint32_t pq = 0;

    auto release_stage = [&](int c, int sv) {
      uint32_t old = 0;
      if (elect_one())
        asm volatile("atom.acq_rel.cta.shared::cta.inc.u32 %0, [%1], 7;" : "=r"(old) : "r"(sb + OFF_CNT + sv * 4) : "memory");
      if (__any_sync(0xffffffffu, old == 7)) {
        if (elect_one()) {
          if (c + 2 < c_end) load_v(sb, maps, sv, row0 + (c + 2) * C);
          if (c + NQ < c_end) load_qkg(sb, maps, sq, row0 + (c + NQ) * C, rank, c + NQ >= c_main);
        }
      }
      if (++sq == NQ) { sq = 0; pq ^= 1; }
    };

#pragma unroll 1
    for (int c = c_begin; c < c_main; c++) {
      const int n = c - c_begin, sv = n & 1;
      const uint32_t qkg = sb + OFF_QKG + sq * QKG_BYTES;
      const uint32_t dq = uniform(desc_k(qkg)), dv = uniform(desc_mn(sb + OFF_V + sv * V_BYTES));
      const uint32_t ea = qkg + E_OFF + eq;
      TRACE(wg, n, 0);
      mbar_wait(sb + BAR_READY + sq * 8, pq);
      TRACE(wg, n, 1);
      mbar_wait(sb + BAR_V + sv * 8, (n >> 1) & 1);
      TRACE(wg, n, 2);
      const bool slow = uniform(lds32(qkg + E_OFF + 2 * EVEC)) != 0;
      scale_state(S0, ea);
      scale_state(S1, ea);
      if (slow) { scale_state(S0, ea + EVEC); scale_state(S1, ea + EVEC); }
      wg_fence();
      gemm_state(S0, dq, dv + mbS * (TILE >> 4));
      gemm_state(S1, dq, dv + mbK * (TILE >> 4));
      wg_commit();
      wg_wait<0>();
      reg_fence(S0);
      reg_fence(S1);
      TRACE(wg, n, 4);
      release_stage(c, sv);
    }
    TRACE(wg, 39, 1);
    if (seg >= 2) {
      const int slot = ((head * 2 + (seg - 2)) * 2 + rank) * 8 + warp;
      if (elect_one()) {
        flag_wait(&g_flag[slot]);
        g_flag[slot] = 0;
      }
      __syncwarp();
      const uint4* src = &g_state[(size_t)slot * 512 + lane];
#pragma unroll
      for (int i = 0; i < 8; i++) {
        const float4 e = lds_f4(sb + OFF_AUXD + eq + i * 16);
        const uint4 a = __ldcg(src + i * 32), b = __ldcg(src + (8 + i) * 32);
        S0[8 * i + 0] += e.x * bf_lo(a.x); S0[8 * i + 1] += e.y * bf_hi(a.x);
        S0[8 * i + 2] += e.x * bf_lo(a.y); S0[8 * i + 3] += e.y * bf_hi(a.y);
        S0[8 * i + 4] += e.z * bf_lo(a.z); S0[8 * i + 5] += e.w * bf_hi(a.z);
        S0[8 * i + 6] += e.z * bf_lo(a.w); S0[8 * i + 7] += e.w * bf_hi(a.w);
        S1[8 * i + 0] += e.x * bf_lo(b.x); S1[8 * i + 1] += e.y * bf_hi(b.x);
        S1[8 * i + 2] += e.x * bf_lo(b.y); S1[8 * i + 3] += e.y * bf_hi(b.y);
        S1[8 * i + 4] += e.z * bf_lo(b.z); S1[8 * i + 5] += e.w * bf_hi(b.z);
        S1[8 * i + 6] += e.z * bf_lo(b.w); S1[8 * i + 7] += e.w * bf_hi(b.w);
      }
    }
    if (seg == 1 || seg == 2) {
      const int slot = ((head * 2 + (seg - 1)) * 2 + rank) * 8 + warp;
      uint4* dst = &g_state[(size_t)slot * 512 + lane];
#pragma unroll
      for (int i = 0; i < 8; i++) {
        const float4 e = lds_f4(sb + OFF_AUXC + eq + i * 16);
        uint4 a, b;
        a.x = pack_bf16(S0[8 * i + 0] * e.x, S0[8 * i + 1] * e.y); a.y = pack_bf16(S0[8 * i + 2] * e.x, S0[8 * i + 3] * e.y);
        a.z = pack_bf16(S0[8 * i + 4] * e.z, S0[8 * i + 5] * e.w); a.w = pack_bf16(S0[8 * i + 6] * e.z, S0[8 * i + 7] * e.w);
        b.x = pack_bf16(S1[8 * i + 0] * e.x, S1[8 * i + 1] * e.y); b.y = pack_bf16(S1[8 * i + 2] * e.x, S1[8 * i + 3] * e.y);
        b.z = pack_bf16(S1[8 * i + 4] * e.z, S1[8 * i + 5] * e.w); b.w = pack_bf16(S1[8 * i + 6] * e.z, S1[8 * i + 7] * e.w);
        __stcg(dst + i * 32, a);
        __stcg(dst + (8 + i) * 32, b);
      }
      __syncwarp();
      if (elect_one()) asm volatile("st.release.gpu.global.u32 [%0], %1;" ::"l"(&g_flag[slot]), "r"(1u) : "memory");
      __syncwarp();
    }
    TRACE(wg, 39, 2);

    asm volatile("barrier.cluster.wait.aligned;" ::: "memory");
    const uint32_t rt = sb + OFF_RECV + wg * TILE;
    const uint32_t slot = rt + lane * 128 + (((2 * w4) ^ (lane & 7)) << 4);
    const uint32_t sma = rt + (((lane >> 4) << 3) + (lane & 7)) * 128 + (((2 * w4 + ((lane >> 3) & 1)) ^ (lane & 7)) << 4);
    const uint32_t peer_delta = mapa(sb, rank ^ 1) - sb;
#pragma unroll 1
    for (int c = c_main; c < c_end; c++) {
      const int n = c - c_begin, sv = n & 1, m = c - c_main;
      const uint32_t qkg = sb + OFF_QKG + sq * QKG_BYTES;
      const uint32_t dq = uniform(desc_k(qkg));
      const uint32_t dvS = uniform(desc_mn(sb + OFF_V + sv * V_BYTES + mbS * TILE));
      const uint32_t dvK = uniform(desc_mn(sb + OFF_V + sv * V_BYTES + mbK * TILE));
      const uint32_t ea = qkg + E_OFF + eq;
      float O[32];
      uint32_t Af[16], Op[16];
      TRACE(wg, n, 0);
      mbar_wait(sb + BAR_READY + sq * 8, pq);
      TRACE(wg, n, 1);
      mbar_wait(sb + BAR_V + sv * 8, (n >> 1) & 1);
      TRACE(wg, n, 2);
      const bool slow = uniform(lds32(qkg + E_OFF + 2 * EVEC)) != 0;
      scale_state(S0, ea);
      cvt_state<0>(Af, S0);
      wg_fence();
      gemm_inter<0>(O, Af, dq);
      wg_commit();
      gemm_intra(O, dq, dvS);
      wg_commit();
      if (w4 == 0) {
        if (elect_one()) {
          mbar_expect_tx(sb + BAR_RECV + wg * 8, TILE);
          if (m > 0) {
            bulk_wait_read0();
            mbar_arrive_remote(sb + BAR_SENDOK + wg * 8 + peer_delta);
          }
        }
      }
      __syncwarp();
      scale_state(S1, ea);
      wg_wait<1>();
      reg_fence(Af);
      cvt_state<1>(Af, S0);
      if (slow) scale_state(S0, ea + EVEC);
      wg_fence();
      gemm_inter<1>(O, Af, dq);
      wg_commit();
      gemm_state(S0, dq, dvS);
      wg_commit();
      wg_wait<1>();
      reg_fence(O);
      reg_fence(Af);
#pragma unroll
      for (int i = 0; i < 16; i++) Op[i] = pack_bf16(O[2 * i], O[2 * i + 1]);
      TRACE(wg, n, 3);
      cvt_state<0>(Af, S1);
      wg_fence();
      gemm_inter<0>(O, Af, dq);
      wg_commit();
      gemm_intra(O, dq, dvK);
      wg_commit();
      if (m >= 1) mbar_wait(sb + BAR_SENDOK + wg * 8, (m - 1) & 1);
#pragma unroll
      for (int i = 0; i < 4; i++)
        st_async_v4(((slot + (i >> 1) * 4096) ^ ((i & 1) << 4)) + peer_delta, Op[4 * i], Op[4 * i + 1], Op[4 * i + 2],
                    Op[4 * i + 3], sb + BAR_RECV + wg * 8 + peer_delta);
      wg_wait<1>();
      reg_fence(Af);
      cvt_state<1>(Af, S1);
      if (slow) scale_state(S1, ea + EVEC);
      wg_fence();
      gemm_inter<1>(O, Af, dq);
      wg_commit();
      gemm_state(S1, dq, dvK);
      wg_commit();
      wg_wait<1>();
      reg_fence(O);
      mbar_wait(sb + BAR_RECV + wg * 8, m & 1);
      TRACE(wg, n, 5);
#pragma unroll
      for (int i = 0; i < 4; i++) {
        const uint4 pv = lds_u4((slot + (i >> 1) * 4096) ^ ((i & 1) << 4));
        Op[4 * i + 0] = add_bf16x2(pack_bf16(O[8 * i + 0], O[8 * i + 1]), pv.x);
        Op[4 * i + 1] = add_bf16x2(pack_bf16(O[8 * i + 2], O[8 * i + 3]), pv.y);
        Op[4 * i + 2] = add_bf16x2(pack_bf16(O[8 * i + 4], O[8 * i + 5]), pv.z);
        Op[4 * i + 3] = add_bf16x2(pack_bf16(O[8 * i + 6], O[8 * i + 7]), pv.w);
      }
      __syncwarp();
#pragma unroll
      for (int i = 0; i < 4; i++) stmatrix_x4_trans(sma + i * 2048, Op[4 * i], Op[4 * i + 1], Op[4 * i + 2], Op[4 * i + 3]);
      fence_proxy_async();
      if (wg == 0) bar_sync128<2>(); else bar_sync128<3>();
      if (w4 == 0) {
        if (elect_one()) {
          tma_store(&maps.o, row0 + c * C, mbK, rt);
          bulk_commit();
        }
      }
      wg_wait<0>();
      reg_fence(Af);
      reg_fence(S0);
      reg_fence(S1);
      TRACE(wg, n, 4);
      release_stage(c, sv);
      TRACE(wg, n, 6);
    }
    if (w4 == 0) {
      if (elect_one()) bulk_wait0();
    }
    TRACE(wg, 39, 3);
    asm volatile("barrier.cluster.arrive.relaxed.aligned;\nbarrier.cluster.wait.aligned;" ::: "memory");
  }
}

typedef CUresult (*EncodeFn)(CUtensorMap*, CUtensorMapDataType, cuuint32_t, void*, const cuuint64_t*, const cuuint64_t*,
                             const cuuint32_t*, const cuuint32_t*, CUtensorMapInterleave, CUtensorMapSwizzle,
                             CUtensorMapL2promotion, CUtensorMapFloatOOBfill);

static void make_map(EncodeFn fn, CUtensorMap* m, const void* ptr, int nblk) {
  cuuint64_t dims[3] = {64, (cuuint64_t)H * T, 4};
  cuuint64_t strides[2] = {(cuuint64_t)D * 2, 128};
  cuuint32_t box[3] = {64, 64, (cuuint32_t)nblk};
  cuuint32_t es[3] = {1, 1, 1};
  fn(m, CU_TENSOR_MAP_DATA_TYPE_BFLOAT16, 3, const_cast<void*>(ptr), dims, strides, box, es, CU_TENSOR_MAP_INTERLEAVE_NONE,
     CU_TENSOR_MAP_SWIZZLE_128B, CU_TENSOR_MAP_L2_PROMOTION_L2_128B, CU_TENSOR_MAP_FLOAT_OOB_FILL_NONE);
}

}

extern "C" void kernel_launch(void* const* d_in, const int* in_sizes, int n_in, void* d_out, int out_size) {
  using namespace gla;
  static EncodeFn fn = nullptr;
  if (!fn) {
    void* p = nullptr;
    cudaDriverEntryPointQueryResult qr;
    cudaGetDriverEntryPoint("cuTensorMapEncodeTiled", &p, cudaEnableDefault, &qr);
    fn = (EncodeFn)p;
    cudaFuncSetAttribute(gla_kernel, cudaFuncAttributeMaxDynamicSharedMemorySize, SMEM_BYTES);
  }
  Maps maps;
  make_map(fn, &maps.q, d_in[0], 2);
  make_map(fn, &maps.k, d_in[1], 2);
  make_map(fn, &maps.v, d_in[2], 4);
  make_map(fn, &maps.g, d_in[3], 2);
  make_map(fn, &maps.o, d_out, 1);
  gla_kernel<<<H * 4 * 2, 384, SMEM_BYTES, cudaStreamPerThread>>>(maps, (const uint32_t*)d_in[0], (const uint32_t*)d_in[1],
                                                                 (const uint32_t*)d_in[3]);
}
```

```cpp
#include <cuda_runtime.h>
#include <cuda_bf16.h>
#include <cuda.h>
#include <stdint.h>

namespace gla {

constexpr int H = 16, T = 2048, D = 256, C = 64, NCHUNK = T / C;

#define PFQ 0
#define PF 0
#define SEG0 8
#define SEG1 8
#define SEG2 8

constexpr uint32_t TILE = 8192;
constexpr uint32_t QKG_BYTES = 6 * TILE;
constexpr uint32_t V_BYTES = 4 * TILE;
constexpr int NQ = 3;
constexpr uint32_t OFF_QKG = 0;
constexpr uint32_t OFF_V = OFF_QKG + NQ * QKG_BYTES;
constexpr uint32_t OFF_RECV = OFF_V + 2 * V_BYTES;
constexpr uint32_t E_OFF = 5 * TILE;
constexpr uint32_t OFF_CARRY = OFF_RECV + 2 * TILE;
constexpr uint32_t OFF_AUXD = OFF_CARRY + 1024;
constexpr uint32_t OFF_AUXC = OFF_AUXD + 512;
constexpr uint32_t OFF_BAR = OFF_AUXC + 512;
constexpr uint32_t BAR_RAW = OFF_BAR;
constexpr uint32_t BAR_READY = BAR_RAW + 8 * NQ;
constexpr uint32_t BAR_EMPTY = BAR_READY + 8 * NQ;
constexpr uint32_t BAR_V = BAR_EMPTY + 8 * NQ;
constexpr uint32_t BAR_RECV = BAR_V + 32;
constexpr uint32_t BAR_SENDOK = BAR_RECV + 16;
constexpr uint32_t BAR_XOK = BAR_SENDOK + 16;
constexpr uint32_t BAR_XRECV = BAR_XOK + 16;
constexpr uint32_t BAR_XOUT = BAR_XRECV + 16;
constexpr uint32_t BAR_XIN = BAR_XOUT + 8;
constexpr uint32_t BAR_PUB = BAR_XIN + 8;
constexpr uint32_t OFF_CNT = BAR_PUB + 16;
constexpr uint32_t SMEM_BYTES = OFF_CNT + 16;
static_assert(SMEM_BYTES <= 232448, "smem");

constexpr uint64_t EVICT_FIRST = 0x12F0000000000000ull;
constexpr float SAFE_LIMIT = 4.611686018427388e18f;
constexpr float NLOG2E = -1.4426950408889634f;

__device__ uint4 g_state[H * 2 * 2 * 16 * 256];
__device__ float4 g_td[H * 2 * 32];
__device__ unsigned int g_flag[H * 4 * 2];
__device__ unsigned int g_done[H * 4 * 2 * 2];
__device__ uint4 g_qt[H * NCHUNK * 2 * 1024];

#define TRACE(role, n, ev)
#define TRACE_ANY(role, n, ev)
#define TRACE_INIT()
#define TRACE_DUMP(role)
constexpr uint32_t SMEM_TOTAL = SMEM_BYTES;
__device__ __forceinline__ uint32_t smem_u32(const void* p) { return (uint32_t)__cvta_generic_to_shared(p); }

__device__ __forceinline__ void mbar_init(uint32_t bar, uint32_t count) {
  asm volatile("mbarrier.init.shared::cta.b64 [%0], %1;" ::"r"(bar), "r"(count) : "memory");
}
__device__ __forceinline__ void mbar_expect_tx(uint32_t bar, uint32_t bytes) {
  asm volatile("mbarrier.arrive.expect_tx.shared::cta.b64 _, [%0], %1;" ::"r"(bar), "r"(bytes) : "memory");
}
__device__ __forceinline__ void mbar_arrive(uint32_t bar) {
  asm volatile("mbarrier.arrive.shared::cta.b64 _, [%0];" ::"r"(bar) : "memory");
}
__device__ __forceinline__ void mbar_arrive_remote(uint32_t remote_bar) {
  asm volatile("mbarrier.arrive.relaxed.cluster.shared::cluster.b64 _, [%0];" ::"r"(remote_bar) : "memory");
}
__device__ __forceinline__ void mbar_wait(uint32_t bar, uint32_t parity) {
  asm volatile(
      "{\n.reg .pred p;\n.reg .u32 n;\nmov.u32 n, 0;\n"
      "WAIT_LOOP:\n"
      "mbarrier.try_wait.parity.shared::cta.b64 p, [%0], %1;\n"
      "@p bra WAIT_DONE;\n"
      "add.u32 n, n, 1;\nsetp.gt.u32 p, n, 4000000;\n@p trap;\n"
      "bra WAIT_LOOP;\n"
      "WAIT_DONE:\n}\n" ::"r"(bar), "r"(parity) : "memory");
}
__device__ __forceinline__ bool mbar_test(uint32_t bar, uint32_t parity) {
  uint32_t r;
  asm volatile("{\n.reg .pred p;\nmbarrier.test_wait.parity.shared::cta.b64 p, [%1], %2;\nselp.u32 %0, 1, 0, p;\n}\n"
               : "=r"(r) : "r"(bar), "r"(parity) : "memory");
  return r != 0;
}
__device__ __forceinline__ void flag_wait(unsigned int* flag, uint32_t val) {
  asm volatile(
      "{\n.reg .pred p;\n.reg .u32 n, f;\nmov.u32 n, 0;\n"
      "WAIT_LOOP:\n"
      "ld.relaxed.gpu.global.u32 f, [%0];\n"
      "setp.eq.u32 p, f, %1;\n"
      "@p bra WAIT_DONE;\n"
      "add.u32 n, n, 1;\nsetp.gt.u32 p, n, 4000000;\n@p trap;\n"
      "bra WAIT_LOOP;\n"
      "WAIT_DONE:\nld.acquire.gpu.global.u32 f, [%0];\nst.relaxed.gpu.global.u32 [%0], 0;\n}\n" ::"l"(flag), "r"(val) : "memory");
}
__device__ __forceinline__ uint32_t mapa(uint32_t addr, uint32_t rank) {
  uint32_t r;
  asm("mapa.shared::cluster.u32 %0, %1, %2;" : "=r"(r) : "r"(addr), "r"(rank));
  return r;
}
__device__ __forceinline__ bool elect_one() {
  uint32_t r;
  asm volatile("{\n.reg .pred p;\nelect.sync _|p, 0xffffffff;\nselp.u32 %0, 1, 0, p;\n}\n" : "=r"(r));
  return r != 0;
}
__device__ __forceinline__ uint32_t uniform(uint32_t v) { return __shfl_sync(0xffffffffu, v, 0); }
__device__ __forceinline__ void fence_proxy_async() { asm volatile("fence.proxy.async.shared::cta;" ::: "memory"); }
template <int ID> __device__ __forceinline__ void bar_sync128() { asm volatile("bar.sync %0, 128;" ::"n"(ID) : "memory"); }
#define TURN 0
__device__ __forceinline__ void turn_wait(int wg) { if (TURN) asm volatile("bar.sync %0, 256;" ::"r"(5 + wg) : "memory"); }
template <int WHEN> __device__ __forceinline__ void turn_pass(int wg) {
  if (TURN && (WHEN == TURN || WHEN == 0)) asm volatile("bar.arrive %0, 256;" ::"r"(6 - wg) : "memory");
}
template <int ID> __device__ __forceinline__ bool bar_red_or128(bool v) {
  uint32_t r;
  asm volatile(
      "{\n.reg .pred p, q;\nsetp.ne.u32 q, %2, 0;\n"
      "bar.red.or.pred p, %1, 128, q;\nselp.u32 %0, 1, 0, p;\n}\n"
      : "=r"(r) : "n"(ID), "r"((uint32_t)v) : "memory");
  return r != 0;
}
__device__ __forceinline__ void tma_load(uint32_t dst, const CUtensorMap* map, int row, int blk, uint32_t bar) {
  asm volatile(
      "cp.async.bulk.tensor.3d.shared::cluster.global.mbarrier::complete_tx::bytes.L2::cache_hint"
      " [%0], [%1, {0, %3, %4}], [%2], %5;"
      ::"r"(dst), "l"((uint64_t)map), "r"(bar), "r"(row), "r"(blk), "l"(EVICT_FIRST) : "memory");
}
__device__ __forceinline__ void tma_prefetch(const CUtensorMap* map, int row, int blk) {
  asm volatile("cp.async.bulk.prefetch.tensor.3d.L2.global.tile.L2::cache_hint [%0, {0, %1, %2}], %3;"
               ::"l"((uint64_t)map), "r"(row), "r"(blk), "l"(EVICT_FIRST) : "memory");
}
__device__ __forceinline__ void tma_store(const CUtensorMap* map, int row, int blk, uint32_t src) {
  asm volatile("cp.async.bulk.tensor.3d.global.shared::cta.bulk_group [%0, {0, %2, %3}], [%1];"
               ::"l"((uint64_t)map), "r"(src), "r"(row), "r"(blk) : "memory");
}
__device__ __forceinline__ void tma_reduce_add(const CUtensorMap* map, int row, int blk, uint32_t src) {
  asm volatile("cp.reduce.async.bulk.tensor.3d.global.shared::cta.add.tile.bulk_group [%0, {0, %2, %3}], [%1];"
               ::"l"((uint64_t)map), "r"(src), "r"(row), "r"(blk) : "memory");
}
__device__ __forceinline__ void bulk_load_pair(uint32_t dst, const void* src, uint32_t bytes, uint32_t bar) {
  asm volatile("cp.async.bulk.shared::cluster.global.mbarrier::complete_tx::bytes.multicast::cluster [%0], [%1], %2, [%3], %4;"
               ::"r"(dst), "l"(src), "r"(bytes), "r"(bar), "h"((uint16_t)3) : "memory");
}
__device__ __forceinline__ void bulk_store(void* dst, uint32_t src, uint32_t bytes) {
  asm volatile("cp.async.bulk.global.shared::cta.bulk_group [%0], [%1], %2;" ::"l"(dst), "r"(src), "r"(bytes) : "memory");
}
__device__ __forceinline__ void bulk_wait_read1() { asm volatile("cp.async.bulk.wait_group.read 1;" ::: "memory"); }
__device__ __forceinline__ void bulk_commit() { asm volatile("cp.async.bulk.commit_group;" ::: "memory"); }
__device__ __forceinline__ void bulk_wait_read0() { asm volatile("cp.async.bulk.wait_group.read 0;" ::: "memory"); }
__device__ __forceinline__ void bulk_wait0() { asm volatile("cp.async.bulk.wait_group 0;" ::: "memory"); }

__device__ __forceinline__ uint32_t lds32(uint32_t a) {
  uint32_t v;
  asm volatile("ld.shared.b32 %0, [%1];" : "=r"(v) : "r"(a));
  return v;
}
__device__ __forceinline__ void sts32(uint32_t a, uint32_t v) { asm volatile("st.shared.b32 [%0], %1;" ::"r"(a), "r"(v)); }
__device__ __forceinline__ void sts_u4(uint32_t a, uint32_t x, uint32_t y, uint32_t z, uint32_t w) {
  asm volatile("st.shared.v4.b32 [%0], {%1, %2, %3, %4};" ::"r"(a), "r"(x), "r"(y), "r"(z), "r"(w));
}
__device__ __forceinline__ void sts16(uint32_t a, uint16_t v) { asm volatile("st.shared.b16 [%0], %1;" ::"r"(a), "h"(v)); }
__device__ __forceinline__ void sts_f2(uint32_t a, float x, float y) {
  asm volatile("st.shared.v2.f32 [%0], {%1, %2};" ::"r"(a), "f"(x), "f"(y));
}
__device__ __forceinline__ float2 lds_f2(uint32_t a) {
  float2 v;
  asm volatile("ld.shared.v2.f32 {%0, %1}, [%2];" : "=f"(v.x), "=f"(v.y) : "r"(a));
  return v;
}
__device__ __forceinline__ float4 lds_f4(uint32_t a) {
  float4 v;
  asm volatile("ld.shared.v4.f32 {%0, %1, %2, %3}, [%4];" : "=f"(v.x), "=f"(v.y), "=f"(v.z), "=f"(v.w) : "r"(a));
  return v;
}
__device__ __forceinline__ uint4 lds_u4(uint32_t a) {
  uint4 v;
  asm volatile("ld.shared.v4.b32 {%0, %1, %2, %3}, [%4];" : "=r"(v.x), "=r"(v.y), "=r"(v.z), "=r"(v.w) : "r"(a));
  return v;
}
__device__ __forceinline__ void st_async_v4(uint32_t remote_addr, uint32_t a, uint32_t b, uint32_t c, uint32_t d,
                                            uint32_t remote_bar) {
  asm volatile("st.async.weak.shared::cluster.mbarrier::complete_tx::bytes.v4.b32 [%0], {%1, %2, %3, %4}, [%5];"
               ::"r"(remote_addr), "r"(a), "r"(b), "r"(c), "r"(d), "r"(remote_bar) : "memory");
}
__device__ __forceinline__ void stmatrix_x4(uint32_t a, uint32_t r0, uint32_t r1, uint32_t r2, uint32_t r3) {
  asm volatile("stmatrix.sync.aligned.m8n8.x4.shared.b16 [%0], {%1, %2, %3, %4};"
               ::"r"(a), "r"(r0), "r"(r1), "r"(r2), "r"(r3) : "memory");
}
__device__ __forceinline__ void ldmatrix_x4(uint32_t a, uint32_t* r) {
  asm volatile("ldmatrix.sync.aligned.m8n8.x4.shared.b16 {%0, %1, %2, %3}, [%4];"
               : "=r"(r[0]), "=r"(r[1]), "=r"(r[2]), "=r"(r[3]) : "r"(a));
}
__device__ __forceinline__ void stmatrix_x4_trans(uint32_t a, uint32_t r0, uint32_t r1, uint32_t r2, uint32_t r3) {
  asm volatile("stmatrix.sync.aligned.m8n8.x4.trans.shared.b16 [%0], {%1, %2, %3, %4};"
               ::"r"(a), "r"(r0), "r"(r1), "r"(r2), "r"(r3) : "memory");
}
__device__ __forceinline__ float ex2f(float x) { float y; asm("ex2.approx.ftz.f32 %0, %1;" : "=f"(y) : "f"(x)); return y; }
__device__ __forceinline__ float rcpf(float x) { float y; asm("rcp.approx.ftz.f32 %0, %1;" : "=f"(y) : "f"(x)); return y; }
__device__ __forceinline__ uint32_t pack_bf16(float lo, float hi) {
  uint32_t r;
  asm("cvt.rn.bf16x2.f32 %0, %1, %2;" : "=r"(r) : "f"(hi), "f"(lo));
  return r;
}
__device__ __forceinline__ uint32_t mul_bf16x2(uint32_t a, uint32_t b) {
  uint32_t r;
  asm("mul.rn.bf16x2 %0, %1, %2;" : "=r"(r) : "r"(a), "r"(b));
  return r;
}
__device__ __forceinline__ uint32_t add_bf16x2(uint32_t a, uint32_t b) {
  uint32_t r;
  asm("add.rn.bf16x2 %0, %1, %2;" : "=r"(r) : "r"(a), "r"(b));
  return r;
}
__device__ __forceinline__ uint16_t lds16(uint32_t a) {
  uint16_t v;
  asm volatile("ld.shared.b16 %0, [%1];" : "=h"(v) : "r"(a));
  return v;
}
__device__ __forceinline__ float bf_lo(uint32_t w) { return __uint_as_float(w << 16); }
__device__ __forceinline__ float bf_hi(uint32_t w) { return __uint_as_float(w & 0xffff0000u); }

__device__ __forceinline__ void wg_fence() { asm volatile("wgmma.fence.sync.aligned;" ::: "memory"); }
__device__ __forceinline__ void wg_commit() { asm volatile("wgmma.commit_group.sync.aligned;" ::: "memory"); }
template <int N> __device__ __forceinline__ void wg_wait() {
  asm volatile("wgmma.wait_group.sync.aligned %0;" ::"n"(N) : "memory");
}
template <int N> __device__ __forceinline__ void reg_fence(float (&r)[N]) {
#pragma unroll
  for (int i = 0; i < N; i++) asm volatile("" : "+f"(r[i])::"memory");
}
template <int N> __device__ __forceinline__ void reg_fence(uint32_t (&r)[N]) {
#pragma unroll
  for (int i = 0; i < N; i++) asm volatile("" : "+r"(r[i])::"memory");
}
__device__ __forceinline__ uint32_t desc_k(uint32_t addr) { return ((addr & 0x3FFFF) >> 4) | (1u << 16); }
__device__ __forceinline__ uint32_t desc_mn(uint32_t addr) { return ((addr & 0x3FFFF) >> 4) | ((TILE >> 4) << 16); }
#define DESC_HI "0x40000040"

#define ACC8(d, o) "+f"(d[o + 0]), "+f"(d[o + 1]), "+f"(d[o + 2]), "+f"(d[o + 3]), "+f"(d[o + 4]), "+f"(d[o + 5]), "+f"(d[o + 6]), "+f"(d[o + 7])
#define ACC32(d) ACC8(d, 0), ACC8(d, 8), ACC8(d, 16), ACC8(d, 24)
#define ACC64(d) ACC32(d), ACC8(d, 32), ACC8(d, 40), ACC8(d, 48), ACC8(d, 56)
#define REGS32 "{%0,%1,%2,%3,%4,%5,%6,%7,%8,%9,%10,%11,%12,%13,%14,%15,%16,%17,%18,%19,%20,%21,%22,%23,%24,%25,%26,%27,%28,%29,%30,%31}"
#define REGS64 "{%0,%1,%2,%3,%4,%5,%6,%7,%8,%9,%10,%11,%12,%13,%14,%15,%16,%17,%18,%19,%20,%21,%22,%23,%24,%25,%26,%27,%28,%29,%30,%31," \
               "%32,%33,%34,%35,%36,%37,%38,%39,%40,%41,%42,%43,%44,%45,%46,%47,%48,%49,%50,%51,%52,%53,%54,%55,%56,%57,%58,%59,%60,%61,%62,%63}"

template <int ACC>
__device__ __forceinline__ void wgmma_n64_rs(float (&d)[32], uint32_t a0, uint32_t a1, uint32_t a2, uint32_t a3,
                                             uint32_t bdesc) {
  asm volatile(
      "{\n.reg .b64 db;\nmov.b64 db, {%36, " DESC_HI "};\n"
      "wgmma.mma_async.sync.aligned.m64n64k16.f32.bf16.bf16 " REGS32 ", {%32,%33,%34,%35}, db, %37, 1, 1, 0;\n}\n"
      : ACC32(d) : "r"(a0), "r"(a1), "r"(a2), "r"(a3), "r"(bdesc), "n"(ACC));
}
template <int TA, int ACC>
__device__ __forceinline__ void wgmma_n64_ss(float (&d)[32], uint32_t adesc, uint32_t bdesc) {
  asm volatile(
      "{\n.reg .b64 da, db;\nmov.b64 da, {%32, " DESC_HI "};\nmov.b64 db, {%33, " DESC_HI "};\n"
      "wgmma.mma_async.sync.aligned.m64n64k16.f32.bf16.bf16 " REGS32 ", da, db, %34, 1, 1, %35, 0;\n}\n"
      : ACC32(d) : "r"(adesc), "r"(bdesc), "n"(ACC), "n"(TA));
}
__device__ __forceinline__ void wgmma_n128_tt(float (&d)[64], uint32_t adesc, uint32_t bdesc) {
  asm volatile(
      "{\n.reg .b64 da, db;\nmov.b64 da, {%64, " DESC_HI "};\nmov.b64 db, {%65, " DESC_HI "};\n"
      "wgmma.mma_async.sync.aligned.m64n128k16.f32.bf16.bf16 " REGS64 ", da, db, 1, 1, 1, 1, 1;\n}\n"
      : ACC64(d) : "r"(adesc), "r"(bdesc));
}

struct Maps { CUtensorMap q, k, g, v, o; };

__device__ __forceinline__ void load_qkg(uint32_t sb, const Maps& m, int stage, int row, int rank) {
  const uint32_t qkg = sb + OFF_QKG + stage * QKG_BYTES, bar = sb + BAR_RAW + stage * 8;
  mbar_expect_tx(bar, 6 * TILE);
  tma_load(qkg + 4 * TILE, &m.g, row, rank * 2, bar);
  tma_load(qkg + 2 * TILE, &m.k, row, rank * 2, bar);
  tma_load(qkg, &m.q, row, rank * 2, bar);
}
__device__ __forceinline__ void prefetch_chunk(const Maps& m, int row, int rank, bool qkg) {
  tma_prefetch(&m.v, row, rank * 2);
  tma_prefetch(&m.v, row, rank * 2 + 1);
  if (qkg) {
    tma_prefetch(&m.g, row, rank * 2);
    tma_prefetch(&m.k, row, rank * 2);
    tma_prefetch(&m.q, row, rank * 2);
  }
}
__device__ __forceinline__ void load_v(uint32_t sb, const Maps& m, int stage, int row, int blk) {
  tma_load(sb + OFF_V + stage * V_BYTES + blk * TILE, &m.v, row, blk, sb + BAR_V + (blk >> 1) * 16 + stage * 8);
}

__device__ __forceinline__ void scale4(float* S, float e0, float e1) { S[0] *= e0; S[1] *= e1; S[2] *= e0; S[3] *= e1; }
__device__ __forceinline__ void scale_one(float (&S)[64], uint32_t eaddr) {
#pragma unroll
  for (int i = 0; i < 4; i++) {
    const uint4 e = lds_u4(eaddr + i * 64);
    const uint32_t w[4] = {e.x, e.y, e.z, e.w};
#pragma unroll
    for (int j = 0; j < 4; j++) scale4(&S[16 * i + 4 * j], __uint_as_float(w[j] << 16), __uint_as_float(w[j]));
  }
}
__device__ __forceinline__ uint32_t enc_decay(float x0, float x1, float& res0, float& res1) {
  x0 *= res0; x1 *= res1;
  const uint32_t lo = pack_bf16(x0, 0.f);
  const int hi = max((int)__float_as_uint(x1) - (int)lo + 0x8000, 0);
  const uint32_t w = ((uint32_t)hi & 0xffff0000u) | lo;
  const float e0 = __uint_as_float(lo << 16), e1 = __uint_as_float(w);
  res0 = e0 > 1e-36f ? x0 * rcpf(e0) : 1.f;
  res1 = e1 > 1e-36f ? x1 * rcpf(e1) : 1.f;
  return w;
}
__device__ __forceinline__ void cvt_state(uint32_t (&Ah)[8], uint32_t (&Af)[16], const float (&S)[64]) {
#pragma unroll
  for (int i = 0; i < 8; i++) Ah[i] = pack_bf16(S[2 * i], S[2 * i + 1]);
#pragma unroll
  for (int i = 0; i < 16; i++) Af[i] = pack_bf16(S[16 + 2 * i], S[16 + 2 * i + 1]);
}

template <bool UPPER>
__device__ __forceinline__ bool prep_half(uint32_t a0, uint32_t a1, float& f0, float& f1) {
  constexpr float INIT = UPPER ? 1.f : 0.0625f;
  constexpr int B0 = UPPER ? 4096 : 3072, STEP = UPPER ? 1024 : -1024;
  constexpr int XO = UPPER ? 2 * TILE : 0, YO = UPPER ? 0 : 2 * TILE;
  float p0 = INIT, p1 = INIT, r0, r1;
  uint32_t gw[8], xw[8], yw[8];
  ldmatrix_x4(a0 + B0 + 4 * TILE, gw);
  ldmatrix_x4(a1 + B0 + 4 * TILE, gw + 4);
#pragma unroll
  for (int b8 = 0; b8 < 4; b8++) {
    const int o = B0 + b8 * STEP;
    float e0[8], e1[8];
    ldmatrix_x4(a0 + o + XO, xw);
    ldmatrix_x4(a1 + o + XO, xw + 4);
    ldmatrix_x4(a0 + o + YO, yw);
    ldmatrix_x4(a1 + o + YO, yw + 4);
#pragma unroll
    for (int i = 0; i < 8; i++) {
      const int t = UPPER ? i : 7 - i;
      e0[t] = ex2f(bf_lo(gw[t]) * NLOG2E);
      e1[t] = ex2f(bf_hi(gw[t]) * NLOG2E);
    }
    if (b8 < 3) {
      ldmatrix_x4(a0 + (o + STEP + 4 * (int)TILE), gw);
      ldmatrix_x4(a1 + (o + STEP + 4 * (int)TILE), gw + 4);
    }
#pragma unroll
    for (int i = 0; i < 8; i++) {
      const int t = UPPER ? i : 7 - i;
      if (UPPER) { p0 = fmaf(p0, e0[t], p0); p1 = fmaf(p1, e1[t], p1); }
      xw[t] = mul_bf16x2(xw[t], pack_bf16(p0, p1));
      if (!UPPER) { p0 = fmaf(p0, e0[t], p0); p1 = fmaf(p1, e1[t], p1); }
    }
    stmatrix_x4(a0 + o + XO, xw[0], xw[1], xw[2], xw[3]);
    stmatrix_x4(a1 + o + XO, xw[4], xw[5], xw[6], xw[7]);
    f0 = rcpf(p0); f1 = rcpf(p1);
    r0 = f0 * 0.0625f; r1 = f1 * 0.0625f;
    if (!UPPER) { f0 = r0; f1 = r1; }
#pragma unroll
    for (int i = 7; i >= 0; i--) {
      const int t = UPPER ? i : 7 - i;
      if (!UPPER) { r0 = fmaf(r0, e0[t], r0); r1 = fmaf(r1, e1[t], r1); }
      yw[t] = mul_bf16x2(yw[t], pack_bf16(r0, r1));
      if (UPPER) { r0 = fmaf(r0, e0[t], r0); r1 = fmaf(r1, e1[t], r1); }
    }
    stmatrix_x4(a0 + o + YO, yw[0], yw[1], yw[2], yw[3]);
    stmatrix_x4(a1 + o + YO, yw[4], yw[5], yw[6], yw[7]);
  }
  return p0 <= SAFE_LIMIT * INIT && p1 <= SAFE_LIMIT * INIT;
}

__device__ __forceinline__ float sigmoid_f(float g) { return rcpf(1.f + ex2f(g * NLOG2E)); }

__device__ __forceinline__ void gemm_qk(float (&acc)[32], uint32_t dq) {
  const uint32_t dk = dq + ((2 * TILE) >> 4);
  wg_fence();
  wgmma_n64_ss<0, 0>(acc, dq, dk);
#pragma unroll
  for (int kk = 1; kk < 8; kk++) {
    const uint32_t off = ((kk >> 2) * TILE + (kk & 3) * 32) >> 4;
    wgmma_n64_ss<0, 1>(acc, dq + off, dk + off);
  }
  wg_commit();
}
template <int ACC>
__device__ __forceinline__ void gemm_inter(float (&O)[32], uint32_t (&Ah)[8], uint32_t (&Af)[16], float (&S)[64],
                                           uint32_t dq, bool slow, uint32_t e2addr) {
  wg_fence();
  wgmma_n64_rs<ACC>(O, Ah[0], Ah[1], Ah[2], Ah[3], dq);
  wgmma_n64_rs<1>(O, Ah[4], Ah[5], Ah[6], Ah[7], dq + 2);
  wg_commit();
#pragma unroll
  for (int kk = 2; kk < 6; kk++)
    wgmma_n64_rs<1>(O, Af[4 * kk - 8], Af[4 * kk - 7], Af[4 * kk - 6], Af[4 * kk - 5], dq + (((kk >> 2) * TILE + (kk & 3) * 32) >> 4));
  wg_commit();
  wg_wait<1>();
  reg_fence(Ah);
#pragma unroll
  for (int i = 0; i < 8; i++) Ah[i] = pack_bf16(S[48 + 2 * i], S[48 + 2 * i + 1]);
  if (slow) scale_one(S, e2addr);
  wg_fence();
  wgmma_n64_rs<1>(O, Ah[0], Ah[1], Ah[2], Ah[3], dq + ((TILE + 64) >> 4));
  wgmma_n64_rs<1>(O, Ah[4], Ah[5], Ah[6], Ah[7], dq + ((TILE + 96) >> 4));
}
template <int ACC>
__device__ __forceinline__ void gemm_corr(float (&O)[32], const uint32_t (&A)[32], uint32_t dq) {
  wg_fence();
  wgmma_n64_rs<ACC>(O, A[0], A[1], A[2], A[3], dq);
#pragma unroll
  for (int kk = 1; kk < 8; kk++)
    wgmma_n64_rs<1>(O, A[4 * kk], A[4 * kk + 1], A[4 * kk + 2], A[4 * kk + 3], dq + (((kk >> 2) * TILE + (kk & 3) * 32) >> 4));
  wg_commit();
}
__device__ __forceinline__ void store_o(const float (&O)[32], uint32_t a) {
#pragma unroll
  for (int i = 0; i < 4; i++)
    stmatrix_x4_trans(a + i * 2048, pack_bf16(O[8 * i], O[8 * i + 1]), pack_bf16(O[8 * i + 2], O[8 * i + 3]),
                      pack_bf16(O[8 * i + 4], O[8 * i + 5]), pack_bf16(O[8 * i + 6], O[8 * i + 7]));
}
__device__ __forceinline__ void axpy_frag(uint32_t* P, const float4& f, const uint4& x) {
  P[0] = add_bf16x2(P[0], pack_bf16(f.x * bf_lo(x.x), f.y * bf_hi(x.x)));
  P[1] = add_bf16x2(P[1], pack_bf16(f.x * bf_lo(x.y), f.y * bf_hi(x.y)));
  P[2] = add_bf16x2(P[2], pack_bf16(f.z * bf_lo(x.z), f.w * bf_hi(x.z)));
  P[3] = add_bf16x2(P[3], pack_bf16(f.z * bf_lo(x.w), f.w * bf_hi(x.w)));
}
__device__ __forceinline__ void gemm_intra(float (&O)[32], uint32_t dq, uint32_t dv) {
  const uint32_t da = dq + ((4 * TILE) >> 4);
#pragma unroll
  for (int ks = 0; ks < 4; ks++) wgmma_n64_ss<1, 1>(O, dv + ks * 128, da + ks * 2);
}
__device__ __forceinline__ void gemm_state(float (&S)[64], uint32_t dq, uint32_t dv) {
  const uint32_t dk = dq + ((2 * TILE) >> 4) + (((TILE >> 4) - 1) << 16);
#pragma unroll
  for (int ks = 0; ks < 4; ks++) wgmma_n128_tt(S, dv + ks * 128, dk + ks * 128);
}

__global__ void __cluster_dims__(2, 1, 1) __launch_bounds__(384, 1)
gla_kernel(const __grid_constant__ Maps maps, const uint32_t* __restrict__ gq, const uint32_t* __restrict__ gk,
           const uint32_t* __restrict__ gg) {
  extern __shared__ __align__(1024) uint8_t smem_raw[];
  const uint32_t sb = smem_u32(smem_raw);
  const int tid = threadIdx.x, lane = tid & 31;
  const int warp = __shfl_sync(0xffffffffu, tid >> 5, 0), wg = warp >> 2;
  uint32_t rank;
  asm("mov.u32 %0, %%cluster_ctarank;" : "=r"(rank));
  const int cid = blockIdx.x >> 1;
  const int head = cid >> 2, seg = cid & 3;
  const int b1 = SEG0, b2 = SEG0 + SEG1, b3 = SEG0 + SEG1 + SEG2;
  const int c_begin = seg == 0 ? 0 : (seg == 1 ? b1 : (seg == 2 ? b2 : b3));
  const int c_end = seg == 0 ? b1 : (seg == 1 ? b2 : (seg == 2 ? b3 : NCHUNK));
  const int c_next = seg == 0 ? b2 : (seg == 1 ? b3 : NCHUNK);
  const int row0 = head * T;
  const int slot0 = head * NCHUNK * 2 + rank;

  TRACE_INIT();
  if (wg < 2) TRACE(wg, 39, 0);
  if (warp == 0) {
    if (elect_one()) {
#pragma unroll
      for (int s = 0; s < NQ; s++) {
        mbar_init(sb + BAR_RAW + s * 8, 1);
        mbar_init(sb + BAR_READY + s * 8, 128);
        mbar_init(sb + BAR_EMPTY + s * 8, 4);
        sts32(sb + OFF_CNT + s * 4, 0);
      }
#pragma unroll
      for (int s = 0; s < 2; s++) {
        mbar_init(sb + BAR_V + s * 16, 1);
        mbar_init(sb + BAR_V + s * 16 + 8, 1);
        mbar_init(sb + BAR_RECV + s * 8, 1);
        mbar_init(sb + BAR_SENDOK + s * 8, 4);
        mbar_init(sb + BAR_XOK + s * 8, 1);
        mbar_init(sb + BAR_XRECV + s * 8, 1);
        mbar_init(sb + BAR_XOUT + s * 8, s ? 1 : 8);
        mbar_init(sb + BAR_PUB + s * 8, 2);
      }

      asm volatile("fence.mbarrier_init.release.cluster;" ::: "memory");
      if (sb & 1023u) asm volatile("trap;");
#pragma unroll 1
      for (int s = 0; s < NQ; s++) {
        load_qkg(sb, maps, s, row0 + (c_begin + s) * C, rank);
        if (s < 2) {
          mbar_expect_tx(sb + BAR_V + s * 8, 2 * TILE);
          mbar_expect_tx(sb + BAR_V + 16 + s * 8, 2 * TILE);
#pragma unroll 1
          for (int b = 0; b < 4; b++) load_v(sb, maps, s, row0 + (c_begin + s) * C, b);
          mbar_expect_tx(sb + BAR_XRECV + s * 8, 2 * TILE + 512);
        }
      }
#pragma unroll 1
      for (int s = 2; s < PF; s++) prefetch_chunk(maps, row0 + (c_begin + s) * C, rank, PFQ && s >= NQ);
    }
  }
  __syncthreads();
  asm volatile("barrier.cluster.arrive.relaxed.aligned;" ::: "memory");

  if (wg == 2) {
    asm volatile("setmaxnreg.dec.sync.aligned.u32 72;");
    const int pw = warp - 8, blk = pw & 1, half = pw >> 1;
    const int cp = blk * 32 + lane;
    const uint32_t lane_off = blk * TILE + lane * 4;
    const uint32_t row_off = blk * TILE + (lane >> 3) * 128 + (((lane & 7) ^ (lane >> 3)) << 4);
    const uint32_t woff = (cp >> 4) * 64 + (cp & 3) * 16 + ((cp >> 2) & 3) * 4;
    float dt0 = 1.f, dt1 = 1.f;
    float res0 = 1.f, res1 = 1.f;
    if (half) sts_f2(sb + OFF_CARRY + 512 + cp * 8, 1.f, 1.f);
    bar_sync128<1>();
    int sq = 0;
    uint32_t pq = 0;
#pragma unroll 1
    for (int c = c_begin; c < c_end; c++) {
      const int n = c - c_begin;
      const uint32_t qkg = sb + OFF_QKG + sq * QKG_BYTES;
      const uint32_t carry_prev = sb + OFF_CARRY + ((n & 1) ^ 1) * 512 + cp * 8;
      const uint32_t carry_cur = sb + OFF_CARRY + (n & 1) * 512 + cp * 8;
      auto publish_q = [&]() {
        const int t7 = tid & 127;
        const uint32_t off = ((t7 >> 3) & 1) * TILE + (t7 >> 4) * 128 + (((t7 & 7) ^ (t7 >> 4)) << 4);
        const uint4 e = lds_u4(qkg + E_OFF + 768 + (t7 & 15) * 16);
        uint4* dst = &g_qt[(size_t)(slot0 + 2 * c) * 1024 + (off >> 4)];
#pragma unroll
        for (int h = 0; h < 4; h++) {
          uint4 v[2];
#pragma unroll
          for (int i = 0; i < 2; i++) v[i] = lds_u4(qkg + off + (2 * h + i) * 1024);
#pragma unroll
          for (int i = 0; i < 2; i++)
            __stcg(dst + (2 * h + i) * 64, make_uint4(mul_bf16x2(v[i].x, e.x), mul_bf16x2(v[i].y, e.y),
                                                      mul_bf16x2(v[i].z, e.z), mul_bf16x2(v[i].w, e.w)));
        }
      };
      TRACE(2, n, 0);
      mbar_wait(sb + BAR_RAW + sq * 8, pq);
      TRACE(2, n, 1);
      float f0, f1;
      bool safe;
      if (half) safe = prep_half<true>(qkg + row_off, qkg + (row_off ^ 64) + 512, f0, f1);
      else safe = prep_half<false>(qkg + row_off, qkg + (row_off ^ 64) + 512, f0, f1);
      TRACE(2, n, 2);
      if (half) sts_f2(carry_cur, f0, f1);
      fence_proxy_async();
      const bool slow = uniform(bar_red_or128<4>(!safe)) != 0;
      TRACE(2, n, 3);
      if (!slow) {
        float acc[32];
        gemm_qk(acc, uniform(desc_k(qkg)));
        if (!half) {
          const float2 cprev = lds_f2(carry_prev);
          f0 *= cprev.x; f1 *= cprev.y;
          sts32(qkg + E_OFF + woff, enc_decay(f0, f1, res0, res1));
          dt0 *= f0; dt1 *= f1;
          sts32(qkg + E_OFF + 768 + cp * 4, pack_bf16(dt0, dt1));
        }
        if (seg > 0) {
          bar_sync128<1>();
          publish_q();
        }
        wg_wait<0>();
        reg_fence(acc);
        int d = pw * 16 + (lane >> 2) - 2 * (lane & 3);
        asm volatile("" : "+r"(d));
        const uint32_t abase = qkg + 4 * TILE + (pw * 16 + (lane & 15)) * 128;
#pragma unroll
        for (int j = 0; j < 8; j += 2) {
          uint32_t r[4];
#pragma unroll
          for (int u = 0; u < 2; u++) {
            const int sc = 8 * (j + u);
            const float* a = &acc[4 * (j + u)];
            r[2 * u + 0] = pack_bf16(sc <= d ? a[0] : 0.f, sc + 1 <= d ? a[1] : 0.f);
            r[2 * u + 1] = pack_bf16(sc - 8 <= d ? a[2] : 0.f, sc - 7 <= d ? a[3] : 0.f);
          }
          stmatrix_x4(abase + (((j + (lane >> 4)) ^ (lane & 7)) << 4), r[0], r[1], r[2], r[3]);
        }
        fence_proxy_async();
      } else {
        const size_t gbase = ((size_t)(row0 + c * C) * D + rank * 128) / 2 + cp;
        const int tb = half * 32;
        const uint32_t la = qkg + lane_off;
        float o0 = 1.f, o1 = 1.f, w0, w1;
#pragma unroll 1
        for (int lev = -1; lev < 7; lev++) {
          const int bm = lev < 0 ? 0 : (1 << lev) - 1;
          if (lev == 6) {
#pragma unroll 1
            for (int i = 0; i < 32; i++) {
              const uint32_t gw = gg[gbase + (size_t)((32 - tb) + i) * 128];
              o0 *= sigmoid_f(bf_lo(gw)); o1 *= sigmoid_f(bf_hi(gw));
            }
          }
          w0 = o0; w1 = o1;
#pragma unroll 1
          for (int i = 0; i < 32; i++) {
            const int t = tb + i;
            const uint32_t gw = gg[gbase + (size_t)t * 128], qw = gq[gbase + (size_t)t * 128];
            if ((t & bm) == 0) { w0 = 1.f; w1 = 1.f; }
            if (lev >= 0) { w0 *= sigmoid_f(bf_lo(gw)); w1 *= sigmoid_f(bf_hi(gw)); }
            sts32((la ^ ((t & 7) << 4)) + t * 128, pack_bf16(bf_lo(qw) * w0 * 0.0625f, bf_hi(qw) * w1 * 0.0625f));
          }
          w0 = o0; w1 = o1;
#pragma unroll 1
          for (int i = 31; i >= 0; i--) {
            const int t = tb + i;
            const uint32_t gw = gg[gbase + (size_t)t * 128], kw = gk[gbase + (size_t)t * 128];
            if ((t & bm) == bm) { w0 = 1.f; w1 = 1.f; }
            sts32((la ^ ((t & 7) << 4)) + t * 128 + 2 * TILE, pack_bf16(bf_lo(kw) * w0, bf_hi(kw) * w1));
            w0 *= sigmoid_f(bf_lo(gw)); w1 *= sigmoid_f(bf_hi(gw));
          }
          if (lev < 6) {
            fence_proxy_async();
            bar_sync128<1>();
            float acc[32];
            gemm_qk(acc, uniform(desc_k(qkg)));
            wg_wait<0>();
            reg_fence(acc);
            const uint32_t tbase = qkg + 5 * TILE + (pw * 16 + (lane & 15)) * 128;
#pragma unroll
            for (int j = 0; j < 8; j += 2)
              stmatrix_x4(tbase + (((j + (lane >> 4)) ^ (lane & 7)) << 4), pack_bf16(acc[4 * j], acc[4 * j + 1]),
                          pack_bf16(acc[4 * j + 2], acc[4 * j + 3]), pack_bf16(acc[4 * j + 4], acc[4 * j + 5]),
                          pack_bf16(acc[4 * j + 6], acc[4 * j + 7]));
            __syncwarp();
#pragma unroll 1
            for (int i = 0; i < 32; i++) {
              const int t = pw * 16 + (i >> 1), sc = (i & 1) * 32 + lane;
              const uint32_t off = t * 128 + (((sc >> 3) ^ (t & 7)) << 4) + (sc & 7) * 2;
              const bool mine = lev < 0 ? (sc >= t) : (sc < t && ((t ^ sc) >> lev) == 1);
              const uint16_t val = sc > t ? (uint16_t)0 : lds16(qkg + 5 * TILE + off);
              if (mine) sts16(qkg + 4 * TILE + off, val);
            }
            bar_sync128<1>();
          }
        }
        if (half) {
          f0 = 1.f; f1 = 1.f;
          sts_f2(carry_cur, 1.f, 1.f);
        } else {
          const float2 cprev = lds_f2(carry_prev);
          const uint32_t wa = enc_decay(cprev.x, cprev.y, res0, res1), wb = enc_decay(w0, w1, res0, res1);
          sts32(qkg + E_OFF + woff, wa);
          sts32(qkg + E_OFF + woff + 256, wb);
          dt0 *= cprev.x; dt1 *= cprev.y;
          sts32(qkg + E_OFF + 768 + cp * 4, pack_bf16(dt0, dt1));
          dt0 *= w0; dt1 *= w1;
        }
        fence_proxy_async();
        bar_sync128<1>();
        if (seg > 0) publish_q();
      }
      if (c == c_end - 1) {
        const uint32_t aoff = (cp >> 3) * 64 + (cp & 3) * 16 + ((cp >> 2) & 1) * 8;
        if (half) {
          sts_f2(sb + OFF_AUXC + aoff, f0, f1);
        } else {
          const float2 cl = lds_f2(carry_cur);
          sts_f2(sb + OFF_AUXD + aoff, dt0 * cl.x, dt1 * cl.y);
        }
      }
      if (tid == 256) sts32(qkg + E_OFF + 512, slow ? 1u : 0u);
      mbar_arrive(sb + BAR_READY + sq * 8);
      TRACE(2, n, 4);
      if (++sq == NQ) { sq = 0; pq ^= 1; }
    }
    bar_sync128<1>();
    if (pw == 0) {
      if (seg < 3 && elect_one()) {
        unsigned int* done = &g_done[((head * 4 + seg + 1) * 2 + rank) * 2];
        uint32_t pe = 0;
        int k3 = 0;
#pragma unroll 1
        for (int c = c_end; c < c_next; c++) {
          const uint32_t qkg = sb + OFF_QKG + sq * QKG_BYTES, bar = sb + BAR_RAW + sq * 8;
          if (c == c_end || c == c_next - 3) {
            flag_wait(done + (c != c_end), 1);
            TRACE_ANY(2, 14, (c != c_end) * 2);
            asm volatile("fence.proxy.async.global;" ::: "memory");
            TRACE_ANY(2, 14, (c != c_end) * 2 + 1);
          }
          mbar_wait(sb + BAR_EMPTY + sq * 8, pe);
          if (c - c_end < 5) TRACE_ANY(2, 13, c - c_end);
          mbar_expect_tx(bar, 4 * TILE);
          bulk_load_pair(qkg + rank * 2 * TILE, &g_qt[(size_t)(slot0 + 2 * c) * 1024], 2 * TILE, bar);
          if (++sq == NQ) sq = 0;
          if (++k3 == NQ) { k3 = 0; pe ^= 1; }
        }
      }
    } else if (pw == 1) {
      if (seg > 0 && elect_one()) {
        unsigned int* done = &g_done[((head * 4 + seg) * 2 + rank) * 2];
        mbar_wait(sb + BAR_PUB, 0);
        TRACE_ANY(2, 15, 0);
        asm volatile("st.release.gpu.global.u32 [%0], 1;" ::"l"(done) : "memory");
        TRACE_ANY(2, 15, 1);
        mbar_wait(sb + BAR_PUB + 8, 0);
        TRACE_ANY(2, 15, 2);
        asm volatile("st.release.gpu.global.u32 [%0], 1;" ::"l"(done + 1) : "memory");
        TRACE_ANY(2, 15, 3);
      }
    } else if (pw == 2) {
      if (seg < 2) {
        if (seg == 1) __stcg(&g_td[(head * 2 + rank) * 32 + lane], lds_f4(sb + OFF_AUXD + lane * 16));
        mbar_wait(sb + BAR_XOUT, 0);
        if (lane == 0) TRACE_ANY(2, 12, 0);
        asm volatile("fence.acq_rel.gpu;" ::: "memory");
        __syncwarp();
        if (lane >= 2 * seg + 2 && lane < 6)
          asm volatile("red.relaxed.gpu.global.add.u32 [%0], 1;" ::"l"(&g_flag[head * 8 + lane]) : "memory");
        if (lane == 0) TRACE_ANY(2, 12, 1);
      }
    } else {
      if ((seg == 1 || seg == 2) && elect_one()) {
        flag_wait(&g_flag[head * 8 + seg * 2 + rank], 2 * seg);
        mbar_arrive(sb + BAR_XIN);
        TRACE_ANY(2, 12, 2);
      }
    }
  } else {
    asm volatile("setmaxnreg.inc.sync.aligned.u32 216;");
    const int w4 = warp & 3;
    const int mbS = 2 * wg + (1 - rank), mbK = 2 * wg + rank;
    const uint32_t slot = sb + OFF_RECV + wg * TILE + (tid & 127) * 16;
    const uint32_t sma = (((lane >> 4) << 3) + (lane & 7)) * 128 + (((2 * w4 + ((lane >> 3) & 1)) ^ (lane & 7)) << 4);
    const uint32_t peer_delta = mapa(sb, rank ^ 1) - sb;
    const int nmain = c_end - c_begin;
    int sq = 0;
    uint32_t pq = 0;
    uint32_t P0[32], P1[32];
    {
      float S0[64], S1[64], O[32];
      uint32_t Ah[8], Af[16];
#pragma unroll
      for (int i = 0; i < 64; i++) { S0[i] = 0.f; S1[i] = 0.f; }
      asm volatile("barrier.cluster.wait.aligned;" ::: "memory");

      auto retire = [&](int m, int sq_prev) {
        fence_proxy_async();
        if (wg == 0) bar_sync128<2>(); else bar_sync128<3>();
        const int svp = (m - 1) & 1, c = c_begin + m;
        if (w4 == 0) {
          if (elect_one()) {
            if (m == nmain - 2) { bulk_wait0(); mbar_arrive(sb + BAR_PUB); }
            tma_store(&maps.o, row0 + (c - 1) * C, mbK, sb + OFF_V + svp * V_BYTES + mbS * TILE);
            bulk_commit();
            if (m + 1 < nmain) {
              mbar_expect_tx(sb + BAR_V + wg * 16 + svp * 8, 2 * TILE);
              load_v(sb, maps, svp, row0 + (c + 1) * C, mbK);
            }
          }
        } else if (w4 == 1) {
          if (elect_one()) {
            if (m + 2 < nmain) {
              uint32_t old;
              asm volatile("atom.relaxed.cta.shared::cta.inc.u32 %0, [%1], 1;" : "=r"(old) : "r"(sb + OFF_CNT + sq_prev * 4) : "memory");
              if (old == 1) load_qkg(sb, maps, sq_prev, row0 + (c + 2) * C, rank);
            } else {
              mbar_arrive(sb + BAR_EMPTY + sq_prev * 8);
              mbar_arrive_remote(sb + BAR_EMPTY + sq_prev * 8 + peer_delta);
            }
          }
        }
      };

      if (wg == 1) turn_pass<0>(1);
      mbar_wait(sb + BAR_READY, 0);
      mbar_wait(sb + BAR_V + wg * 16, 0);
      bool slow = uniform(lds32(sb + OFF_QKG + E_OFF + 512)) != 0;
#pragma unroll 1
      for (int m = 0; m < nmain; m++) {
        const int sv = m & 1;
        const uint32_t qkg = sb + OFF_QKG + sq * QKG_BYTES;
        const uint32_t dq = uniform(desc_k(qkg));
        const uint32_t dvS = uniform(desc_mn(sb + OFF_V + sv * V_BYTES + mbS * TILE));
        const uint32_t dvK = uniform(desc_mn(sb + OFF_V + sv * V_BYTES + mbK * TILE));
        const uint32_t ea = qkg + E_OFF + (lane & 3) * 16;
        TRACE(wg, m, 0);
        wg_wait<1>();
        cvt_state(Ah, Af, S0);
        reg_fence(Ah);
        reg_fence(Af);
        turn_wait(wg);
        TRACE(wg, m, 1);
        gemm_inter<0>(O, Ah, Af, S0, dq, slow, ea + 256);
        gemm_intra(O, dq, dvS);
        wg_commit();
        gemm_state(S0, dq, dvS);
        wg_commit();
        turn_pass<1>(wg);
        reg_fence(S1);
        if (m > 0) retire(m, sq == 0 ? NQ - 1 : sq - 1);
        if (w4 == 2) {
          if (elect_one()) mbar_expect_tx(sb + BAR_RECV + wg * 8, TILE);
        }
        if (PF && warp == 3 && m + PF < nmain) {
          if (elect_one()) prefetch_chunk(maps, row0 + (c_begin + m + PF) * C, rank, PFQ);
        }
        __syncwarp();
        scale_one(S1, ea);
        if (m > 0) mbar_wait(sb + BAR_SENDOK + wg * 8, (m - 1) & 1);
        TRACE(wg, m, 2);
        wg_wait<1>();
        reg_fence(O);
        reg_fence(Af);
        reg_fence(Ah);
        turn_pass<2>(wg);
        TRACE(wg, m, 3);
#pragma unroll
        for (int i = 0; i < 4; i++)
          st_async_v4(slot + i * 2048 + peer_delta, pack_bf16(O[8 * i], O[8 * i + 1]), pack_bf16(O[8 * i + 2], O[8 * i + 3]),
                      pack_bf16(O[8 * i + 4], O[8 * i + 5]), pack_bf16(O[8 * i + 6], O[8 * i + 7]),
                      sb + BAR_RECV + wg * 8 + peer_delta);
        if (w4 == 0 && m > 0) {
          if (elect_one()) {
            bulk_wait_read0();
            if (m + 1 < nmain) load_v(sb, maps, sv ^ 1, row0 + (c_begin + m + 1) * C, mbS);
            else mbar_arrive_remote(sb + BAR_XOK + wg * 8 + peer_delta);
          }
        }
        __syncwarp();
        cvt_state(Ah, Af, S1);
        mbar_wait(sb + BAR_RECV + wg * 8, m & 1);
#pragma unroll
        for (int i = 0; i < 4; i++) {
          const uint4 pv = lds_u4(slot + i * 2048);
          O[8 * i + 0] = bf_lo(pv.x); O[8 * i + 1] = bf_hi(pv.x); O[8 * i + 2] = bf_lo(pv.y); O[8 * i + 3] = bf_hi(pv.y);
          O[8 * i + 4] = bf_lo(pv.z); O[8 * i + 5] = bf_hi(pv.z); O[8 * i + 6] = bf_lo(pv.w); O[8 * i + 7] = bf_hi(pv.w);
        }
        reg_fence(O);
        reg_fence(Ah);
        reg_fence(Af);
        TRACE(wg, m, 4);
        turn_wait(wg);
        TRACE(wg, m, 5);
        gemm_inter<1>(O, Ah, Af, S1, dq, slow, ea + 256);
        gemm_intra(O, dq, dvK);
        wg_commit();
        gemm_state(S1, dq, dvK);
        wg_commit();
        if (wg == 0 || m + 1 < nmain) turn_pass<1>(wg);
        reg_fence(S0);
        if (elect_one()) mbar_arrive_remote(sb + BAR_SENDOK + wg * 8 + peer_delta);
        if (++sq == NQ) { sq = 0; pq ^= 1; }
        if (m + 1 < nmain) {
          const uint32_t qn = sb + OFF_QKG + sq * QKG_BYTES + E_OFF;
          mbar_wait(sb + BAR_READY + sq * 8, pq);
          slow = uniform(lds32(qn + 512)) != 0;
          scale_one(S0, qn + (lane & 3) * 16);
          mbar_wait(sb + BAR_V + wg * 16 + (sv ^ 1) * 8, ((m + 1) >> 1) & 1);
        }
        TRACE(wg, m, 6);
        wg_wait<1>();
        reg_fence(O);
        reg_fence(Af);
        reg_fence(Ah);
        if (wg == 0 || m + 1 < nmain) turn_pass<2>(wg);
        TRACE(wg, m, 7);
        store_o(O, sb + OFF_V + sv * V_BYTES + mbS * TILE + sma);
      }
      wg_wait<0>();
      reg_fence(S1);
      retire(nmain, sq == 0 ? NQ - 1 : sq - 1);
      TRACE(wg, 39, 1);
#pragma unroll
      for (int i = 0; i < 8; i++) {
        const float4 e = lds_f4(sb + OFF_AUXC + (lane & 3) * 16 + i * 64);
        P1[4 * i + 0] = pack_bf16(S0[8 * i + 0] * e.x, S0[8 * i + 1] * e.y); P1[4 * i + 1] = pack_bf16(S0[8 * i + 2] * e.x, S0[8 * i + 3] * e.y);
        P1[4 * i + 2] = pack_bf16(S0[8 * i + 4] * e.z, S0[8 * i + 5] * e.w); P1[4 * i + 3] = pack_bf16(S0[8 * i + 6] * e.z, S0[8 * i + 7] * e.w);
        P0[4 * i + 0] = pack_bf16(S1[8 * i + 0] * e.x, S1[8 * i + 1] * e.y); P0[4 * i + 1] = pack_bf16(S1[8 * i + 2] * e.x, S1[8 * i + 3] * e.y);
        P0[4 * i + 2] = pack_bf16(S1[8 * i + 4] * e.z, S1[8 * i + 5] * e.w); P0[4 * i + 3] = pack_bf16(S1[8 * i + 6] * e.z, S1[8 * i + 7] * e.w);
      }
    }
    if (seg < 3) {
      const uint32_t xrecv = sb + OFF_V + (nmain & 1) * V_BYTES + wg * 2 * TILE + (tid & 127) * 16;
      const uint32_t xa = (lane & 3) * 16;
      uint32_t bx, tx;
      asm volatile("mov.u32 %0, %%ctaid.x;" : "=r"(bx));
      asm volatile("mov.u32 %0, %%tid.x;" : "=r"(tx));
      uint4* gs = &g_state[(size_t)(bx >> 3) * (4 * 4096) + tx];
      TRACE(wg, 39, 4);
      if (seg < 2) {
        uint4* dst = gs + (bx & 3) * 4096;
#pragma unroll
        for (int i = 0; i < 8; i++) {
          __stcg(dst + i * 256, make_uint4(P0[4 * i], P0[4 * i + 1], P0[4 * i + 2], P0[4 * i + 3]));
          __stcg(dst + (8 + i) * 256, make_uint4(P1[4 * i], P1[4 * i + 1], P1[4 * i + 2], P1[4 * i + 3]));
        }
        __syncwarp();
        if (elect_one()) mbar_arrive(sb + BAR_XOUT);
      }
      mbar_wait(sb + BAR_XOK + wg * 8, 0);
#pragma unroll
      for (int i = 0; i < 8; i++)
        st_async_v4(xrecv + i * 2048 + peer_delta, P1[4 * i], P1[4 * i + 1], P1[4 * i + 2], P1[4 * i + 3],
                    sb + BAR_XRECV + wg * 8 + peer_delta);
      if (w4 == 0) {
        const float4 td = lds_f4(sb + OFF_AUXD + lane * 16);
        st_async_v4(sb + OFF_CARRY + wg * 512 + lane * 16 + peer_delta, __float_as_uint(td.x), __float_as_uint(td.y),
                    __float_as_uint(td.z), __float_as_uint(td.w), sb + BAR_XRECV + wg * 8 + peer_delta);
      }
      TRACE(wg, 39, 5);
      mbar_wait(sb + BAR_XRECV + wg * 8, 0);
      TRACE(wg, 39, 6);
#pragma unroll
      for (int i = 0; i < 8; i++) {
        const uint4 v = lds_u4(xrecv + i * 2048);
        P1[4 * i] = v.x; P1[4 * i + 1] = v.y; P1[4 * i + 2] = v.z; P1[4 * i + 3] = v.w;
      }
      if (seg > 0) {
        mbar_wait(sb + BAR_XIN, 0);
        TRACE(wg, 39, 7);
        const uint32_t rk = bx & 1;
        const uint4* own = gs + rk * 4096;
        const uint4* oth = gs + (rk ^ 1) * 4096 + 2048;
        const float4* dp = &g_td[(bx >> 3) * 64 + (tx & 3)];
#pragma unroll 1
        for (int src = 0; src < seg; src++) {
          uint4 x[16];
#pragma unroll
          for (int i = 0; i < 8; i++) { x[i] = __ldcg(own + src * 8192 + i * 256); x[8 + i] = __ldcg(oth + src * 8192 + i * 256); }
#pragma unroll
          for (int i = 0; i < 8; i++) {
            float4 f0 = lds_f4(sb + OFF_AUXD + xa + i * 64), f1 = lds_f4(sb + OFF_CARRY + wg * 512 + xa + i * 64);
            if (src + 2 == seg) {
              const float4 d0 = __ldcg(dp + rk * 32 + i * 4), d1 = __ldcg(dp + (rk ^ 1) * 32 + i * 4);
              f0.x *= d0.x; f0.y *= d0.y; f0.z *= d0.z; f0.w *= d0.w;
              f1.x *= d1.x; f1.y *= d1.y; f1.z *= d1.z; f1.w *= d1.w;
            }
            axpy_frag(&P0[4 * i], f0, x[i]);
            axpy_frag(&P1[4 * i], f1, x[8 + i]);
          }
        }
      }
      TRACE(wg, 39, 2);
      const int ncorr = c_next - c_end;
      const uint32_t tileA = sb + OFF_RECV + wg * TILE;
      const uint32_t tileB = sb + OFF_QKG + ((sq + wg) % NQ) * QKG_BYTES + 4 * TILE;
      if (wg == 1) asm volatile("bar.arrive 7, 256;" ::: "memory");
      mbar_wait(sb + BAR_RAW + sq * 8, pq);
#pragma unroll 1
      for (int k = 0; k < ncorr; k++) {
        const uint32_t dq = uniform(desc_k(sb + OFF_QKG + sq * QKG_BYTES));
        const uint32_t tile = (k & 1) ? tileB : tileA;
        const int sq_cur = sq;
        float O[32];
        TRACE(wg, nmain + k, 0);
        asm volatile("bar.sync %0, 256;" ::"r"(7 + wg) : "memory");
        gemm_corr<0>(O, P0, dq + rank * ((2 * TILE) >> 4));
        gemm_corr<1>(O, P1, dq + (rank ^ 1) * ((2 * TILE) >> 4));
        if (wg == 0 || k + 1 < ncorr) asm volatile("bar.arrive %0, 256;" ::"r"(8 - wg) : "memory");
        TRACE(wg, nmain + k, 1);
        if (++sq == NQ) { sq = 0; pq ^= 1; }
        if (k + 1 < ncorr) mbar_wait(sb + BAR_RAW + sq * 8, pq);
        wg_wait<0>();
        reg_fence(O);
        TRACE(wg, nmain + k, 2);
        store_o(O, tile + sma);
        fence_proxy_async();
        if (w4 == 0) {
          if (elect_one()) {
            if (k == 0) { bulk_wait0(); mbar_arrive(sb + BAR_PUB + 8); } else bulk_wait_read0();
          }
        }
        if (wg == 0) bar_sync128<2>(); else bar_sync128<3>();
        if (w4 == 0) {
          if (elect_one()) {
            tma_reduce_add(&maps.o, row0 + (c_end + k) * C, mbK, tile);
            bulk_commit();
          }
        }
        if (w4 == 1 && k + NQ < ncorr) {
          if (elect_one()) {
            mbar_arrive(sb + BAR_EMPTY + sq_cur * 8);
            mbar_arrive_remote(sb + BAR_EMPTY + sq_cur * 8 + peer_delta);
          }
        }
        __syncwarp();
        TRACE(wg, nmain + k, 3);
      }
    }
    if (w4 == 0) {
      if (elect_one()) {
        bulk_wait0();
        if (seg == 3) mbar_arrive(sb + BAR_PUB + 8);
      }
    }
    TRACE(wg, 39, 3);
    TRACE_DUMP(wg);
    if (wg == 0) TRACE_DUMP(2);
    asm volatile("barrier.cluster.arrive.relaxed.aligned;\nbarrier.cluster.wait.aligned;" ::: "memory");
  }
}

typedef CUresult (*EncodeFn)(CUtensorMap*, CUtensorMapDataType, cuuint32_t, void*, const cuuint64_t*, const cuuint64_t*,
                             const cuuint32_t*, const cuuint32_t*, CUtensorMapInterleave, CUtensorMapSwizzle,
                             CUtensorMapL2promotion, CUtensorMapFloatOOBfill);

static void make_map(EncodeFn fn, CUtensorMap* m, const void* ptr, int nblk) {
  cuuint64_t dims[3] = {64, (cuuint64_t)H * T, 4};
  cuuint64_t strides[2] = {(cuuint64_t)D * 2, 128};
  cuuint32_t box[3] = {64, 64, (cuuint32_t)nblk};
  cuuint32_t es[3] = {1, 1, 1};
  fn(m, CU_TENSOR_MAP_DATA_TYPE_BFLOAT16, 3, const_cast<void*>(ptr), dims, strides, box, es, CU_TENSOR_MAP_INTERLEAVE_NONE,
     CU_TENSOR_MAP_SWIZZLE_128B, CU_TENSOR_MAP_L2_PROMOTION_L2_128B, CU_TENSOR_MAP_FLOAT_OOB_FILL_NONE);
}

}

extern "C" void kernel_launch(void* const* d_in, const int* in_sizes, int n_in, void* d_out, int out_size) {
  using namespace gla;
  static EncodeFn fn = nullptr;
  if (!fn) {
    void* p = nullptr;
    cudaDriverEntryPointQueryResult qr;
    cudaGetDriverEntryPoint("cuTensorMapEncodeTiled", &p, cudaEnableDefault, &qr);
    fn = (EncodeFn)p;
    cudaFuncSetAttribute(gla_kernel, cudaFuncAttributeMaxDynamicSharedMemorySize, SMEM_TOTAL);
  }
  Maps maps;
  make_map(fn, &maps.q, d_in[0], 2);
  make_map(fn, &maps.k, d_in[1], 2);
  make_map(fn, &maps.v, d_in[2], 1);
  make_map(fn, &maps.g, d_in[3], 2);
  make_map(fn, &maps.o, d_out, 1);
  gla_kernel<<<H * 4 * 2, 384, SMEM_TOTAL, cudaStreamPerThread>>>(maps, (const uint32_t*)d_in[0], (const uint32_t*)d_in[1],
                                                                 (const uint32_t*)d_in[3]);
}
```

```cpp
#include <cuda_runtime.h>
#include <cuda_bf16.h>
#include <cuda.h>
#include <stdint.h>

namespace gla {

constexpr int H = 16, T = 2048, D = 256, C = 64, NCHUNK = T / C;

#define PFQ 0
#define PF 0
constexpr int SEGC = NCHUNK / 4;

constexpr uint32_t TILE = 8192;
constexpr uint32_t QKG_BYTES = 6 * TILE;
constexpr uint32_t V_BYTES = 4 * TILE;
constexpr int NQ = 3;
constexpr uint32_t OFF_QKG = 0;
constexpr uint32_t OFF_V = OFF_QKG + NQ * QKG_BYTES;
constexpr uint32_t OFF_RECV = OFF_V + 2 * V_BYTES;
constexpr uint32_t E_OFF = 5 * TILE;
constexpr uint32_t OFF_TD = OFF_QKG + E_OFF + 2048;
constexpr uint32_t OFF_CARRY = OFF_RECV + 2 * TILE;
constexpr uint32_t OFF_AUXD = OFF_CARRY + 1024;
constexpr uint32_t OFF_AUXC = OFF_AUXD + 512;
constexpr uint32_t BAR_XIN1 = OFF_AUXC + 256;
constexpr uint32_t BAR_VT = OFF_AUXC + 320;
constexpr uint32_t OFF_BAR = OFF_AUXC + 512;
constexpr uint32_t BAR_RAW = OFF_BAR;
constexpr uint32_t BAR_READY = BAR_RAW + 8 * NQ;
constexpr uint32_t BAR_EMPTY = BAR_READY + 8 * NQ;
constexpr uint32_t BAR_V = BAR_EMPTY + 8 * NQ;
constexpr uint32_t BAR_RECV = BAR_V + 32;
constexpr uint32_t BAR_SENDOK = BAR_RECV + 16;
constexpr uint32_t BAR_XOK = BAR_SENDOK + 16;
constexpr uint32_t BAR_XRECV = BAR_XOK + 16;
constexpr uint32_t BAR_XOUT = BAR_XRECV + 16;
constexpr uint32_t BAR_XIN = BAR_XOUT + 8;
constexpr uint32_t BAR_PUB = BAR_XIN + 8;
constexpr uint32_t BAR_AOK = BAR_PUB + 16;
constexpr uint32_t OFF_CNT = BAR_AOK + 8 * NQ;
constexpr uint32_t SMEM_BYTES = OFF_CNT + 16;
static_assert(SMEM_BYTES <= 232448, "smem");

constexpr uint64_t EVICT_FIRST = 0x12F0000000000000ull;
constexpr uint64_t EVICT_NORMAL = 0x1000000000000000ull;
#define VKPOL EVICT_FIRST
constexpr float SAFE_LIMIT = 4.611686018427388e18f;
constexpr float NLOG2E = -1.4426950408889634f;

__device__ uint4 g_state[H * 2 * 2 * 16 * 256];
__device__ unsigned int g_epoch[H];
__device__ uint4 g_hint[H * 2 * 2 * 8 * 2];
__device__ float4 g_td[H * 2 * 32];
__device__ unsigned int g_flag[H * 2];
__device__ __align__(8) unsigned int g_done[H * 4 * 2 * 2];
__device__ uint4 g_qt[H * NCHUNK * 2 * 1024];

#define TRACE(role, n, ev)
#define TRACE_ANY(role, n, ev)
#define TRACE_INIT()
#define TRACE_DUMP(role)
constexpr uint32_t SMEM_TOTAL = SMEM_BYTES;
__device__ __forceinline__ uint32_t smem_u32(const void* p) { return (uint32_t)__cvta_generic_to_shared(p); }

__device__ __forceinline__ void mbar_init(uint32_t bar, uint32_t count) {
  asm volatile("mbarrier.init.shared::cta.b64 [%0], %1;" ::"r"(bar), "r"(count) : "memory");
}
__device__ __forceinline__ void mbar_expect_tx(uint32_t bar, uint32_t bytes) {
  asm volatile("mbarrier.arrive.expect_tx.shared::cta.b64 _, [%0], %1;" ::"r"(bar), "r"(bytes) : "memory");
}
__device__ __forceinline__ void mbar_arrive(uint32_t bar) {
  asm volatile("mbarrier.arrive.shared::cta.b64 _, [%0];" ::"r"(bar) : "memory");
}
__device__ __forceinline__ void mbar_arrive_remote(uint32_t remote_bar) {
  asm volatile("mbarrier.arrive.relaxed.cluster.shared::cluster.b64 _, [%0];" ::"r"(remote_bar) : "memory");
}
__device__ __forceinline__ void mbar_wait(uint32_t bar, uint32_t parity) {
  asm volatile(
      "{\n.reg .pred p;\n.reg .u32 n;\nmov.u32 n, 0;\n"
      "WAIT_LOOP:\n"
      "mbarrier.try_wait.parity.shared::cta.b64 p, [%0], %1;\n"
      "@p bra WAIT_DONE;\n"
      "add.u32 n, n, 1;\nsetp.gt.u32 p, n, 4000000;\n@p trap;\n"
      "bra WAIT_LOOP;\n"
      "WAIT_DONE:\n}\n" ::"r"(bar), "r"(parity) : "memory");
}
__device__ __forceinline__ bool mbar_test(uint32_t bar, uint32_t parity) {
  uint32_t r;
  asm volatile("{\n.reg .pred p;\nmbarrier.test_wait.parity.shared::cta.b64 p, [%1], %2;\nselp.u32 %0, 1, 0, p;\n}\n"
               : "=r"(r) : "r"(bar), "r"(parity) : "memory");
  return r != 0;
}
__device__ __forceinline__ void flag_wait(unsigned int* flag, uint32_t val) {
  asm volatile(
      "{\n.reg .pred p;\n.reg .u32 n, f;\nmov.u32 n, 0;\n"
      "WAIT_LOOP:\n"
      "ld.relaxed.gpu.global.u32 f, [%0];\n"
      "setp.eq.u32 p, f, %1;\n"
      "@p bra WAIT_DONE;\n"
      "add.u32 n, n, 1;\nsetp.gt.u32 p, n, 4000000;\n@p trap;\n"
      "bra WAIT_LOOP;\n"
      "WAIT_DONE:\nld.acquire.gpu.global.u32 f, [%0];\nst.relaxed.gpu.global.u32 [%0], 0;\n}\n" ::"l"(flag), "r"(val) : "memory");
}
__device__ __forceinline__ void st_tagged(uint4* p, uint32_t a, uint32_t b, uint32_t c, uint32_t d, uint32_t tag) {
  asm volatile("{\n.reg .b64 x, y;\nmov.b64 x, {%1, %2};\nmov.b64 y, {%3, %4};\nst.relaxed.gpu.global.v2.b64 [%0], {x, y};\n}\n"
               ::"l"(p), "r"((a & ~1u) | tag), "r"(b), "r"((c & ~1u) | tag), "r"(d) : "memory");
}
__device__ __forceinline__ uint4 ld_tagged(const uint4* p) {
  uint4 v;
  asm volatile("{\n.reg .b64 x, y;\nld.relaxed.gpu.global.v2.b64 {x, y}, [%4];\nmov.b64 {%0, %1}, x;\nmov.b64 {%2, %3}, y;\n}\n"
               : "=r"(v.x), "=r"(v.y), "=r"(v.z), "=r"(v.w) : "l"(p) : "memory");
  return v;
}
__device__ __forceinline__ void tag_wait(const uint4* p, uint32_t tag) {
  asm volatile(
      "{\n.reg .pred p;\n.reg .u32 n, f;\nmov.u32 n, 0;\n"
      "WAIT_LOOP:\n"
      "ld.relaxed.gpu.global.u32 f, [%0];\n"
      "and.b32 f, f, 1;\nsetp.eq.u32 p, f, %1;\n"
      "@p bra WAIT_DONE;\n"
      "add.u32 n, n, 1;\nsetp.gt.u32 p, n, 4000000;\n@p trap;\n"
      "bra WAIT_LOOP;\n"
      "WAIT_DONE:\n}\n" ::"l"(p), "r"(tag) : "memory");
}
__device__ __forceinline__ uint32_t ctr_wait(const unsigned int* ctr, uint32_t val) {
  uint32_t f;
  asm volatile(
      "{\n.reg .pred p;\n.reg .u32 n;\nmov.u32 n, 0;\n"
      "WAIT_LOOP:\n"
      "ld.relaxed.gpu.global.u32 %0, [%1];\n"
      "setp.gt.u32 p, %0, %2;\n"
      "@p bra WAIT_DONE;\n"
      "add.u32 n, n, 1;\nsetp.gt.u32 p, n, 4000000;\n@p trap;\n"
      "bra WAIT_LOOP;\n"
      "WAIT_DONE:\nld.acquire.gpu.global.u32 %0, [%1];\n}\n" : "=r"(f) : "l"(ctr), "r"(val) : "memory");
  return f;
}
__device__ __forceinline__ uint32_t cta_id() {
  uint32_t r;
  asm volatile("mov.u32 %0, %%ctaid.x;" : "=r"(r));
  return r;
}
__device__ __forceinline__ uint32_t mapa(uint32_t addr, uint32_t rank) {
  uint32_t r;
  asm("mapa.shared::cluster.u32 %0, %1, %2;" : "=r"(r) : "r"(addr), "r"(rank));
  return r;
}
__device__ __forceinline__ bool elect_one() {
  uint32_t r;
  asm volatile("{\n.reg .pred p;\nelect.sync _|p, 0xffffffff;\nselp.u32 %0, 1, 0, p;\n}\n" : "=r"(r));
  return r != 0;
}
__device__ __forceinline__ uint32_t uniform(uint32_t v) { return __shfl_sync(0xffffffffu, v, 0); }
__device__ __forceinline__ void fence_proxy_async() { asm volatile("fence.proxy.async.shared::cta;" ::: "memory"); }
template <int ID> __device__ __forceinline__ void bar_sync128() { asm volatile("bar.sync %0, 128;" ::"n"(ID) : "memory"); }
#define TURN 0
__device__ __forceinline__ void turn_wait(int wg) { if (TURN) asm volatile("bar.sync %0, 256;" ::"r"(5 + wg) : "memory"); }
template <int WHEN> __device__ __forceinline__ void turn_pass(int wg) {
  if (TURN && (WHEN == TURN || WHEN == 0)) asm volatile("bar.arrive %0, 256;" ::"r"(6 - wg) : "memory");
}
template <int ID> __device__ __forceinline__ bool bar_red_or128(bool v) {
  uint32_t r;
  asm volatile(
      "{\n.reg .pred p, q;\nsetp.ne.u32 q, %2, 0;\n"
      "bar.red.or.pred p, %1, 128, q;\nselp.u32 %0, 1, 0, p;\n}\n"
      : "=r"(r) : "n"(ID), "r"((uint32_t)v) : "memory");
  return r != 0;
}
template <uint64_t POLICY = EVICT_FIRST>
__device__ __forceinline__ void tma_load(uint32_t dst, const CUtensorMap* map, int row, int blk, uint32_t bar) {
  asm volatile(
      "cp.async.bulk.tensor.3d.shared::cluster.global.mbarrier::complete_tx::bytes.L2::cache_hint"
      " [%0], [%1, {0, %3, %4}], [%2], %5;"
      ::"r"(dst), "l"((uint64_t)map), "r"(bar), "r"(row), "r"(blk), "l"(POLICY) : "memory");
}
__device__ __forceinline__ void tma_prefetch(const CUtensorMap* map, int row, int blk) {
  asm volatile("cp.async.bulk.prefetch.tensor.3d.L2.global.tile.L2::cache_hint [%0, {0, %1, %2}], %3;"
               ::"l"((uint64_t)map), "r"(row), "r"(blk), "l"(EVICT_FIRST) : "memory");
}
__device__ __forceinline__ void tma_store(const CUtensorMap* map, int row, int blk, uint32_t src) {
  asm volatile("cp.async.bulk.tensor.3d.global.shared::cta.bulk_group [%0, {0, %2, %3}], [%1];"
               ::"l"((uint64_t)map), "r"(src), "r"(row), "r"(blk) : "memory");
}
__device__ __forceinline__ void tma_reduce_add(const CUtensorMap* map, int row, int blk, uint32_t src) {
  asm volatile("cp.reduce.async.bulk.tensor.3d.global.shared::cta.add.tile.bulk_group [%0, {0, %2, %3}], [%1];"
               ::"l"((uint64_t)map), "r"(src), "r"(row), "r"(blk) : "memory");
}
__device__ __forceinline__ void bulk_load_pair(uint32_t dst, const void* src, uint32_t bytes, uint32_t bar) {
  asm volatile("cp.async.bulk.shared::cluster.global.mbarrier::complete_tx::bytes.multicast::cluster [%0], [%1], %2, [%3], %4;"
               ::"r"(dst), "l"(src), "r"(bytes), "r"(bar), "h"((uint16_t)3) : "memory");
}
__device__ __forceinline__ void bulk_store(void* dst, uint32_t src, uint32_t bytes) {
  asm volatile("cp.async.bulk.global.shared::cta.bulk_group [%0], [%1], %2;" ::"l"(dst), "r"(src), "r"(bytes) : "memory");
}
__device__ __forceinline__ void bulk_wait_read1() { asm volatile("cp.async.bulk.wait_group.read 1;" ::: "memory"); }
__device__ __forceinline__ void bulk_commit() { asm volatile("cp.async.bulk.commit_group;" ::: "memory"); }
__device__ __forceinline__ void bulk_wait_read0() { asm volatile("cp.async.bulk.wait_group.read 0;" ::: "memory"); }
__device__ __forceinline__ void bulk_wait0() { asm volatile("cp.async.bulk.wait_group 0;" ::: "memory"); }

__device__ __forceinline__ uint32_t lds32(uint32_t a) {
  uint32_t v;
  asm volatile("ld.shared.b32 %0, [%1];" : "=r"(v) : "r"(a));
  return v;
}
__device__ __forceinline__ void sts32(uint32_t a, uint32_t v) { asm volatile("st.shared.b32 [%0], %1;" ::"r"(a), "r"(v)); }
__device__ __forceinline__ void sts_u4(uint32_t a, uint32_t x, uint32_t y, uint32_t z, uint32_t w) {
  asm volatile("st.shared.v4.b32 [%0], {%1, %2, %3, %4};" ::"r"(a), "r"(x), "r"(y), "r"(z), "r"(w));
}
__device__ __forceinline__ void sts16(uint32_t a, uint16_t v) { asm volatile("st.shared.b16 [%0], %1;" ::"r"(a), "h"(v)); }
__device__ __forceinline__ void sts_f2(uint32_t a, float x, float y) {
  asm volatile("st.shared.v2.f32 [%0], {%1, %2};" ::"r"(a), "f"(x), "f"(y));
}
__device__ __forceinline__ float2 lds_f2(uint32_t a) {
  float2 v;
  asm volatile("ld.shared.v2.f32 {%0, %1}, [%2];" : "=f"(v.x), "=f"(v.y) : "r"(a));
  return v;
}
__device__ __forceinline__ float4 lds_f4(uint32_t a) {
  float4 v;
  asm volatile("ld.shared.v4.f32 {%0, %1, %2, %3}, [%4];" : "=f"(v.x), "=f"(v.y), "=f"(v.z), "=f"(v.w) : "r"(a));
  return v;
}
__device__ __forceinline__ uint4 lds_u4(uint32_t a) {
  uint4 v;
  asm volatile("ld.shared.v4.b32 {%0, %1, %2, %3}, [%4];" : "=r"(v.x), "=r"(v.y), "=r"(v.z), "=r"(v.w) : "r"(a));
  return v;
}
__device__ __forceinline__ void st_async_v4(uint32_t remote_addr, uint32_t a, uint32_t b, uint32_t c, uint32_t d,
                                            uint32_t remote_bar) {
  asm volatile("st.async.weak.shared::cluster.mbarrier::complete_tx::bytes.v4.b32 [%0], {%1, %2, %3, %4}, [%5];"
               ::"r"(remote_addr), "r"(a), "r"(b), "r"(c), "r"(d), "r"(remote_bar) : "memory");
}
__device__ __forceinline__ void stmatrix_x4(uint32_t a, uint32_t r0, uint32_t r1, uint32_t r2, uint32_t r3) {
  asm volatile("stmatrix.sync.aligned.m8n8.x4.shared.b16 [%0], {%1, %2, %3, %4};"
               ::"r"(a), "r"(r0), "r"(r1), "r"(r2), "r"(r3) : "memory");
}
__device__ __forceinline__ void ldmatrix_x4(uint32_t a, uint32_t* r) {
  asm volatile("ldmatrix.sync.aligned.m8n8.x4.shared.b16 {%0, %1, %2, %3}, [%4];"
               : "=r"(r[0]), "=r"(r[1]), "=r"(r[2]), "=r"(r[3]) : "r"(a));
}
__device__ __forceinline__ void stmatrix_x4_trans(uint32_t a, uint32_t r0, uint32_t r1, uint32_t r2, uint32_t r3) {
  asm volatile("stmatrix.sync.aligned.m8n8.x4.trans.shared.b16 [%0], {%1, %2, %3, %4};"
               ::"r"(a), "r"(r0), "r"(r1), "r"(r2), "r"(r3) : "memory");
}
__device__ __forceinline__ float ex2f(float x) { float y; asm("ex2.approx.ftz.f32 %0, %1;" : "=f"(y) : "f"(x)); return y; }
__device__ __forceinline__ float rcpf(float x) { float y; asm("rcp.approx.ftz.f32 %0, %1;" : "=f"(y) : "f"(x)); return y; }
__device__ __forceinline__ uint32_t pack_bf16(float lo, float hi) {
  uint32_t r;
  asm("cvt.rn.bf16x2.f32 %0, %1, %2;" : "=r"(r) : "f"(hi), "f"(lo));
  return r;
}
__device__ __forceinline__ uint32_t mul_bf16x2(uint32_t a, uint32_t b) {
  uint32_t r;
  asm("mul.rn.bf16x2 %0, %1, %2;" : "=r"(r) : "r"(a), "r"(b));
  return r;
}
__device__ __forceinline__ uint32_t add_bf16x2(uint32_t a, uint32_t b) {
  uint32_t r;
  asm("add.rn.bf16x2 %0, %1, %2;" : "=r"(r) : "r"(a), "r"(b));
  return r;
}
__device__ __forceinline__ uint16_t lds16(uint32_t a) {
  uint16_t v;
  asm volatile("ld.shared.b16 %0, [%1];" : "=h"(v) : "r"(a));
  return v;
}
__device__ __forceinline__ float bf_lo(uint32_t w) { return __uint_as_float(w << 16); }
__device__ __forceinline__ float bf_hi(uint32_t w) { return __uint_as_float(w & 0xffff0000u); }

__device__ __forceinline__ void wg_fence() { asm volatile("wgmma.fence.sync.aligned;" ::: "memory"); }
__device__ __forceinline__ void wg_commit() { asm volatile("wgmma.commit_group.sync.aligned;" ::: "memory"); }
template <int N> __device__ __forceinline__ void wg_wait() {
  asm volatile("wgmma.wait_group.sync.aligned %0;" ::"n"(N) : "memory");
}
template <int N> __device__ __forceinline__ void reg_fence(float (&r)[N]) {
#pragma unroll
  for (int i = 0; i < N; i++) asm volatile("" : "+f"(r[i])::"memory");
}
template <int N> __device__ __forceinline__ void reg_fence(uint32_t (&r)[N]) {
#pragma unroll
  for (int i = 0; i < N; i++) asm volatile("" : "+r"(r[i])::"memory");
}
__device__ __forceinline__ uint32_t desc_k(uint32_t addr) { return ((addr & 0x3FFFF) >> 4) | (1u << 16); }
__device__ __forceinline__ uint32_t desc_mn(uint32_t addr) { return ((addr & 0x3FFFF) >> 4) | ((TILE >> 4) << 16); }
#define DESC_HI "0x40000040"

#define ACC8(d, o) "+f"(d[o + 0]), "+f"(d[o + 1]), "+f"(d[o + 2]), "+f"(d[o + 3]), "+f"(d[o + 4]), "+f"(d[o + 5]), "+f"(d[o + 6]), "+f"(d[o + 7])
#define ACC32(d) ACC8(d, 0), ACC8(d, 8), ACC8(d, 16), ACC8(d, 24)
#define ACC64(d) ACC32(d), ACC8(d, 32), ACC8(d, 40), ACC8(d, 48), ACC8(d, 56)
#define REGS32 "{%0,%1,%2,%3,%4,%5,%6,%7,%8,%9,%10,%11,%12,%13,%14,%15,%16,%17,%18,%19,%20,%21,%22,%23,%24,%25,%26,%27,%28,%29,%30,%31}"
#define REGS64 "{%0,%1,%2,%3,%4,%5,%6,%7,%8,%9,%10,%11,%12,%13,%14,%15,%16,%17,%18,%19,%20,%21,%22,%23,%24,%25,%26,%27,%28,%29,%30,%31," \
               "%32,%33,%34,%35,%36,%37,%38,%39,%40,%41,%42,%43,%44,%45,%46,%47,%48,%49,%50,%51,%52,%53,%54,%55,%56,%57,%58,%59,%60,%61,%62,%63}"

template <int ACC>
__device__ __forceinline__ void wgmma_n64_rs(float (&d)[32], uint32_t a0, uint32_t a1, uint32_t a2, uint32_t a3,
                                             uint32_t bdesc) {
  asm volatile(
      "{\n.reg .b64 db;\nmov.b64 db, {%36, " DESC_HI "};\n"
      "wgmma.mma_async.sync.aligned.m64n64k16.f32.bf16.bf16 " REGS32 ", {%32,%33,%34,%35}, db, %37, 1, 1, 0;\n}\n"
      : ACC32(d) : "r"(a0), "r"(a1), "r"(a2), "r"(a3), "r"(bdesc), "n"(ACC));
}
template <int TA, int ACC>
__device__ __forceinline__ void wgmma_n64_ss(float (&d)[32], uint32_t adesc, uint32_t bdesc) {
  asm volatile(
      "{\n.reg .b64 da, db;\nmov.b64 da, {%32, " DESC_HI "};\nmov.b64 db, {%33, " DESC_HI "};\n"
      "wgmma.mma_async.sync.aligned.m64n64k16.f32.bf16.bf16 " REGS32 ", da, db, %34, 1, 1, %35, 0;\n}\n"
      : ACC32(d) : "r"(adesc), "r"(bdesc), "n"(ACC), "n"(TA));
}
__device__ __forceinline__ void wgmma_n128_tt(float (&d)[64], uint32_t adesc, uint32_t bdesc) {
  asm volatile(
      "{\n.reg .b64 da, db;\nmov.b64 da, {%64, " DESC_HI "};\nmov.b64 db, {%65, " DESC_HI "};\n"
      "wgmma.mma_async.sync.aligned.m64n128k16.f32.bf16.bf16 " REGS64 ", da, db, 1, 1, 1, 1, 1;\n}\n"
      : ACC64(d) : "r"(adesc), "r"(bdesc));
}

struct Maps { CUtensorMap q, k, g, v, o; };

__device__ __forceinline__ void load_qkg(uint32_t sb, const Maps& m, int stage, int row, int rank) {
  const uint32_t qkg = sb + OFF_QKG + stage * QKG_BYTES, bar = sb + BAR_RAW + stage * 8;
  mbar_expect_tx(bar, 6 * TILE);
  tma_load(qkg + 4 * TILE, &m.g, row, rank * 2, bar);
  tma_load(qkg + 2 * TILE, &m.k, row, rank * 2, bar);
  tma_load(qkg, &m.q, row, rank * 2, bar);
}
__device__ __forceinline__ void prefetch_chunk(const Maps& m, int row, int rank, bool qkg) {
  tma_prefetch(&m.v, row, rank * 2);
  tma_prefetch(&m.v, row, rank * 2 + 1);
  if (qkg) {
    tma_prefetch(&m.g, row, rank * 2);
    tma_prefetch(&m.k, row, rank * 2);
    tma_prefetch(&m.q, row, rank * 2);
  }
}
template <uint64_t POLICY = EVICT_FIRST>
__device__ __forceinline__ void load_v(uint32_t sb, const Maps& m, int stage, int row, int blk) {
  mbar_expect_tx(sb + BAR_VT + blk * 16 + stage * 8, TILE);
  tma_load<POLICY>(sb + OFF_V + stage * V_BYTES + blk * TILE, &m.v, row, blk, sb + BAR_VT + blk * 16 + stage * 8);
}

__device__ __forceinline__ void scale4(float* S, float e0, float e1) { S[0] *= e0; S[1] *= e1; S[2] *= e0; S[3] *= e1; }
__device__ __forceinline__ void scale_one(float (&S)[64], uint32_t eaddr) {
#pragma unroll
  for (int i = 0; i < 4; i++) {
    const uint4 e = lds_u4(eaddr + i * 64);
    const uint32_t w[4] = {e.x, e.y, e.z, e.w};
#pragma unroll
    for (int j = 0; j < 4; j++) scale4(&S[16 * i + 4 * j], __uint_as_float(w[j] << 16), __uint_as_float(w[j]));
  }
}
__device__ __forceinline__ void scale_regs(float (&S)[64], const uint32_t (&w)[16]) {
#pragma unroll
  for (int j = 0; j < 16; j++) scale4(&S[4 * j], __uint_as_float(w[j] << 16), __uint_as_float(w[j]));
}
__device__ __forceinline__ uint32_t enc_decay(float x0, float x1, float& res0, float& res1) {
  x0 *= res0; x1 *= res1;
  const uint32_t lo = pack_bf16(x0, 0.f);
  const int hi = max((int)__float_as_uint(x1) - (int)lo + 0x8000, 0);
  const uint32_t w = ((uint32_t)hi & 0xffff0000u) | lo;
  const float e0 = __uint_as_float(lo << 16), e1 = __uint_as_float(w);
  res0 = e0 > 1e-36f ? x0 * rcpf(e0) : 1.f;
  res1 = e1 > 1e-36f ? x1 * rcpf(e1) : 1.f;
  return w;
}
__device__ __forceinline__ void cvt_state(uint32_t (&Ah)[8], uint32_t (&Af)[16], const float (&S)[64]) {
#pragma unroll
  for (int i = 0; i < 8; i++) Ah[i] = pack_bf16(S[2 * i], S[2 * i + 1]);
#pragma unroll
  for (int i = 0; i < 16; i++) Af[i] = pack_bf16(S[16 + 2 * i], S[16 + 2 * i + 1]);
}

template <bool UPPER>
__device__ __forceinline__ bool prep_half(uint32_t a0, uint32_t a1, float& f0, float& f1) {
  constexpr float INIT = UPPER ? 1.f : 0.0625f;
  constexpr int B0 = UPPER ? 4096 : 3072, STEP = UPPER ? 1024 : -1024;
  constexpr int XO = UPPER ? 2 * TILE : 0, YO = UPPER ? 0 : 2 * TILE;
  float p0 = INIT, p1 = INIT, r0, r1;
  uint32_t gw[8], xw[8], yw[8];
  ldmatrix_x4(a0 + B0 + 4 * TILE, gw);
  ldmatrix_x4(a1 + B0 + 4 * TILE, gw + 4);
#pragma unroll
  for (int b8 = 0; b8 < 4; b8++) {
    const int o = B0 + b8 * STEP;
    float e0[8], e1[8];
    ldmatrix_x4(a0 + o + XO, xw);
    ldmatrix_x4(a1 + o + XO, xw + 4);
    ldmatrix_x4(a0 + o + YO, yw);
    ldmatrix_x4(a1 + o + YO, yw + 4);
#pragma unroll
    for (int i = 0; i < 8; i++) {
      const int t = UPPER ? i : 7 - i;
      e0[t] = ex2f(bf_lo(gw[t]) * NLOG2E);
      e1[t] = ex2f(bf_hi(gw[t]) * NLOG2E);
    }
    if (b8 < 3) {
      ldmatrix_x4(a0 + (o + STEP + 4 * (int)TILE), gw);
      ldmatrix_x4(a1 + (o + STEP + 4 * (int)TILE), gw + 4);
    }
#pragma unroll
    for (int i = 0; i < 8; i++) {
      const int t = UPPER ? i : 7 - i;
      if (UPPER) { p0 = fmaf(p0, e0[t], p0); p1 = fmaf(p1, e1[t], p1); }
      xw[t] = mul_bf16x2(xw[t], pack_bf16(p0, p1));
      if (!UPPER) { p0 = fmaf(p0, e0[t], p0); p1 = fmaf(p1, e1[t], p1); }
    }
    stmatrix_x4(a0 + o + XO, xw[0], xw[1], xw[2], xw[3]);
    stmatrix_x4(a1 + o + XO, xw[4], xw[5], xw[6], xw[7]);
    f0 = rcpf(p0); f1 = rcpf(p1);
    r0 = f0 * 0.0625f; r1 = f1 * 0.0625f;
    if (!UPPER) { f0 = r0; f1 = r1; }
#pragma unroll
    for (int i = 7; i >= 0; i--) {
      const int t = UPPER ? i : 7 - i;
      if (!UPPER) { r0 = fmaf(r0, e0[t], r0); r1 = fmaf(r1, e1[t], r1); }
      yw[t] = mul_bf16x2(yw[t], pack_bf16(r0, r1));
      if (UPPER) { r0 = fmaf(r0, e0[t], r0); r1 = fmaf(r1, e1[t], r1); }
    }
    stmatrix_x4(a0 + o + YO, yw[0], yw[1], yw[2], yw[3]);
    stmatrix_x4(a1 + o + YO, yw[4], yw[5], yw[6], yw[7]);
  }
  return p0 <= SAFE_LIMIT * INIT && p1 <= SAFE_LIMIT * INIT;
}

__device__ __forceinline__ float sigmoid_f(float g) { return rcpf(1.f + ex2f(g * NLOG2E)); }

__device__ __forceinline__ void gemm_qk(float (&acc)[32], uint32_t dq) {
  const uint32_t dk = dq + ((2 * TILE) >> 4);
  wg_fence();
  wgmma_n64_ss<0, 0>(acc, dq, dk);
#pragma unroll
  for (int kk = 1; kk < 8; kk++) {
    const uint32_t off = ((kk >> 2) * TILE + (kk & 3) * 32) >> 4;
    wgmma_n64_ss<0, 1>(acc, dq + off, dk + off);
  }
  wg_commit();
}
template <bool WAITV>
__device__ __forceinline__ void gemm_inter(float (&O)[32], uint32_t (&Ah)[8], uint32_t (&Af)[16], float (&S)[64],
                                           uint32_t dq, bool slow, uint32_t e2addr, uint32_t vbar, uint32_t vpar,
                                           uint32_t abar, uint32_t apar) {
  wg_fence();
  wgmma_n64_rs<0>(O, Ah[0], Ah[1], Ah[2], Ah[3], dq);
  wgmma_n64_rs<1>(O, Ah[4], Ah[5], Ah[6], Ah[7], dq + 2);
  wg_commit();
#pragma unroll
  for (int kk = 2; kk < 6; kk++)
    wgmma_n64_rs<1>(O, Af[4 * kk - 8], Af[4 * kk - 7], Af[4 * kk - 6], Af[4 * kk - 5], dq + (((kk >> 2) * TILE + (kk & 3) * 32) >> 4));
  wg_commit();
  if (WAITV) {
    const bool a = mbar_test(abar, apar);
    mbar_wait(vbar, vpar);
    if (!a) mbar_wait(abar, apar);
  } else {
    mbar_wait(vbar, vpar);
  }
  wg_wait<1>();
  reg_fence(Ah);
#pragma unroll
  for (int i = 0; i < 8; i++) Ah[i] = pack_bf16(S[48 + 2 * i], S[48 + 2 * i + 1]);
  if (slow) scale_one(S, e2addr);
  wg_fence();
  wgmma_n64_rs<1>(O, Ah[0], Ah[1], Ah[2], Ah[3], dq + ((TILE + 64) >> 4));
  wgmma_n64_rs<1>(O, Ah[4], Ah[5], Ah[6], Ah[7], dq + ((TILE + 96) >> 4));
}
template <int ACC>
__device__ __forceinline__ void gemm_corr(float (&O)[32], const uint32_t (&A)[32], uint32_t dq) {
  wg_fence();
  wgmma_n64_rs<ACC>(O, A[0], A[1], A[2], A[3], dq);
#pragma unroll
  for (int kk = 1; kk < 8; kk++)
    wgmma_n64_rs<1>(O, A[4 * kk], A[4 * kk + 1], A[4 * kk + 2], A[4 * kk + 3], dq + (((kk >> 2) * TILE + (kk & 3) * 32) >> 4));
  wg_commit();
}
__device__ __forceinline__ void store_o(const float (&O)[32], uint32_t a) {
#pragma unroll
  for (int i = 0; i < 4; i++)
    stmatrix_x4_trans(a + i * 2048, pack_bf16(O[8 * i], O[8 * i + 1]), pack_bf16(O[8 * i + 2], O[8 * i + 3]),
                      pack_bf16(O[8 * i + 4], O[8 * i + 5]), pack_bf16(O[8 * i + 6], O[8 * i + 7]));
}
__device__ __forceinline__ uint32_t fma_bf16x2(uint32_t a, uint32_t b, uint32_t c) {
  uint32_t r;
  asm("fma.rn.bf16x2 %0, %1, %2, %3;" : "=r"(r) : "r"(a), "r"(b), "r"(c));
  return r;
}
__device__ __forceinline__ void axpy_frag(uint32_t* P, const float4& f, const uint4& x) {
  const uint32_t lo = pack_bf16(f.x, f.y), hi = pack_bf16(f.z, f.w);
  P[0] = fma_bf16x2(lo, x.x, P[0]);
  P[1] = fma_bf16x2(lo, x.y, P[1]);
  P[2] = fma_bf16x2(hi, x.z, P[2]);
  P[3] = fma_bf16x2(hi, x.w, P[3]);
}
__device__ __forceinline__ void gemm_intra(float (&O)[32], uint32_t dq, uint32_t dv) {
  const uint32_t da = dq + ((4 * TILE) >> 4);
#pragma unroll
  for (int ks = 0; ks < 4; ks++) wgmma_n64_ss<1, 1>(O, dv + ks * 128, da + ks * 2);
}
__device__ __forceinline__ void gemm_state(float (&S)[64], uint32_t dq, uint32_t dv) {
  const uint32_t dk = dq + ((2 * TILE) >> 4) + (((TILE >> 4) - 1) << 16);
#pragma unroll
  for (int ks = 0; ks < 4; ks++) wgmma_n128_tt(S, dv + ks * 128, dk + ks * 128);
}

__global__ void __cluster_dims__(2, 1, 1) __launch_bounds__(384, 1)
gla_kernel(const __grid_constant__ Maps maps, const uint32_t* __restrict__ gq, const uint32_t* __restrict__ gk,
           const uint32_t* __restrict__ gg) {
  extern __shared__ __align__(1024) uint8_t smem_raw[];
  const uint32_t sb = smem_u32(smem_raw);
  const int tid = threadIdx.x, lane = tid & 31;
  const int warp = __shfl_sync(0xffffffffu, tid >> 5, 0), wg = warp >> 2;
  uint32_t rank;
  asm("mov.u32 %0, %%cluster_ctarank;" : "=r"(rank));
  const int cid = blockIdx.x >> 1;
  const int head = cid >> 2, seg = cid & 3;
  const int c_begin = seg * SEGC, c_end = c_begin + SEGC, c_next = c_end + SEGC;
  const int row0 = head * T;
  const int slot0 = head * NCHUNK * 2 + rank;

  TRACE_INIT();
  if (wg < 2) TRACE(wg, 39, 0);
  if (warp == 0) {
    if (elect_one()) {
      mbar_init(sb + BAR_RAW, 1);
      asm volatile("fence.mbarrier_init.release.cluster;" ::: "memory");
      load_qkg(sb, maps, 0, row0 + c_begin * C, rank);
#pragma unroll
      for (int s = 0; s < NQ; s++) {
        if (s) mbar_init(sb + BAR_RAW + s * 8, 1);
        mbar_init(sb + BAR_READY + s * 8, 4);
        mbar_init(sb + BAR_EMPTY + s * 8, 4);
        mbar_init(sb + BAR_AOK + s * 8, 4);
        sts32(sb + OFF_CNT + s * 4, 0);
      }
#pragma unroll
      for (int s = 0; s < 2; s++) {
#pragma unroll
        for (int b = 0; b < 4; b++) mbar_init(sb + BAR_VT + b * 16 + s * 8, 1);
        mbar_init(sb + BAR_RECV + s * 8, 1);
        mbar_init(sb + BAR_SENDOK + s * 8, 4);
        mbar_init(sb + BAR_XOK + s * 8, 1);
        mbar_init(sb + BAR_XRECV + s * 8, 1);
        mbar_init(sb + BAR_XOUT + s * 8, 1);
        mbar_init(sb + BAR_PUB + s * 8, 2);
      }

      mbar_init(sb + BAR_XIN1, 1);
      asm volatile("fence.mbarrier_init.release.cluster;" ::: "memory");
      if (sb & 1023u) asm volatile("trap;");
#pragma unroll 1
      for (int s = 0; s < NQ; s++) {
        if (s) load_qkg(sb, maps, s, row0 + (c_begin + s) * C, rank);
        if (s < 2) {
#pragma unroll 1
          for (int b = 0; b < 4; b++) load_v(sb, maps, s, row0 + (c_begin + s) * C, b);
          mbar_expect_tx(sb + BAR_XRECV + s * 8, 2 * TILE + 512);
          mbar_expect_tx(sb + BAR_RECV + s * 8, TILE);
        }
      }
    }
  } else if (warp < 5 && lane == 0) {
    const CUtensorMap* mp = warp == 1 ? &maps.k : (warp == 2 ? &maps.q : (warp == 3 ? &maps.v : &maps.o));
    asm volatile("prefetch.tensormap [%0];" ::"l"((uint64_t)mp) : "memory");
  }
  __syncthreads();
  asm volatile("barrier.cluster.arrive.relaxed.aligned;" ::: "memory");

  if (wg == 2) {
    asm volatile("setmaxnreg.dec.sync.aligned.u32 72;");
    const int pw = warp - 8, blk = pw & 1, half = pw >> 1;
    const int cp = blk * 32 + lane;
    const uint32_t lane_off = blk * TILE + lane * 4;
    const uint32_t row_off = blk * TILE + (lane >> 3) * 128 + (((lane & 7) ^ (lane >> 3)) << 4);
    const uint32_t woff = (cp >> 4) * 64 + (cp & 3) * 16 + ((cp >> 2) & 3) * 4;
    float dt0 = 1.f, dt1 = 1.f;
    float res0 = 1.f, res1 = 1.f;
    if (half) sts_f2(sb + OFF_CARRY + 512 + cp * 8, 1.f, 1.f);
    bar_sync128<1>();
    int sq = 0;
    uint32_t pq = 0;
#pragma unroll 1
    for (int c = c_begin; c < c_end; c++) {
      const int n = c - c_begin;
      const uint32_t qkg = sb + OFF_QKG + sq * QKG_BYTES;
      const uint32_t carry_prev = sb + OFF_CARRY + ((n & 1) ^ 1) * 512 + cp * 8;
      const uint32_t carry_cur = sb + OFF_CARRY + (n & 1) * 512 + cp * 8;
      auto operands_ready = [&](bool slow) {
        if (c == c_end - 1) {
          const uint32_t aoff = (cp >> 3) * 64 + (cp & 3) * 16 + ((cp >> 2) & 1) * 8;
          if (!half) {
            const float2 cl = lds_f2(carry_cur);
            sts32(sb + OFF_AUXC + woff, enc_decay(cl.x, cl.y, res0, res1));
            sts_f2(sb + OFF_AUXD + aoff, dt0 * cl.x, dt1 * cl.y);
          }
        }
        if (tid == 256) sts32(qkg + E_OFF + 512, slow ? 1u : 0u);
        __syncwarp();
        if (lane == 0) mbar_arrive(sb + BAR_READY + sq * 8);
        __syncwarp();
      };
      TRACE(2, n, 0);
      mbar_wait(sb + BAR_RAW + sq * 8, pq);
      TRACE(2, n, 1);
      float f0, f1;
      bool safe;
      if (half) safe = prep_half<true>(qkg + row_off, qkg + (row_off ^ 64) + 512, f0, f1);
      else safe = prep_half<false>(qkg + row_off, qkg + (row_off ^ 64) + 512, f0, f1);
      TRACE(2, n, 2);
      if (half) sts_f2(carry_cur, f0, f1);
      fence_proxy_async();
      const bool slow = __any_sync(0xffffffffu, bar_red_or128<4>(!safe));
      TRACE(2, n, 3);
      if (!slow) {
        float acc[32];
        gemm_qk(acc, desc_k(qkg));
        if (!half) {
          const float2 cprev = lds_f2(carry_prev);
          f0 *= cprev.x; f1 *= cprev.y;
          sts32(qkg + E_OFF + woff, enc_decay(f0, f1, res0, res1));
          dt0 *= f0; dt1 *= f1;
          sts32(qkg + E_OFF + 768 + cp * 4, pack_bf16(dt0, dt1));
        }
        operands_ready(false);
        wg_wait<0>();
        reg_fence(acc);
        int d = pw * 16 + (lane >> 2) - 2 * (lane & 3);
        asm volatile("" : "+r"(d));
        const uint32_t abase = qkg + 4 * TILE + (pw * 16 + (lane & 15)) * 128;
#pragma unroll
        for (int j = 0; j < 8; j += 2) {
          uint32_t r[4];
#pragma unroll
          for (int u = 0; u < 2; u++) {
            const int sc = 8 * (j + u);
            const float* a = &acc[4 * (j + u)];
            r[2 * u + 0] = pack_bf16(sc <= d ? a[0] : 0.f, sc + 1 <= d ? a[1] : 0.f);
            r[2 * u + 1] = pack_bf16(sc - 8 <= d ? a[2] : 0.f, sc - 7 <= d ? a[3] : 0.f);
          }
          stmatrix_x4(abase + (((j + (lane >> 4)) ^ (lane & 7)) << 4), r[0], r[1], r[2], r[3]);
        }
        fence_proxy_async();
      } else {
        const size_t gbase = ((size_t)(row0 + c * C) * D + rank * 128) / 2 + cp;
        const int tb = half * 32;
        const uint32_t la = qkg + lane_off;
        float o0 = 1.f, o1 = 1.f, w0, w1;
#pragma unroll 1
        for (int lev = -1; lev < 7; lev++) {
          const int bm = lev < 0 ? 0 : (1 << lev) - 1;
          if (lev == 6) {
#pragma unroll 1
            for (int i = 0; i < 32; i++) {
              const uint32_t gw = gg[gbase + (size_t)((32 - tb) + i) * 128];
              o0 *= sigmoid_f(bf_lo(gw)); o1 *= sigmoid_f(bf_hi(gw));
            }
          }
          w0 = o0; w1 = o1;
#pragma unroll 1
          for (int i = 0; i < 32; i++) {
            const int t = tb + i;
            const uint32_t gw = gg[gbase + (size_t)t * 128], qw = gq[gbase + (size_t)t * 128];
            if ((t & bm) == 0) { w0 = 1.f; w1 = 1.f; }
            if (lev >= 0) { w0 *= sigmoid_f(bf_lo(gw)); w1 *= sigmoid_f(bf_hi(gw)); }
            sts32((la ^ ((t & 7) << 4)) + t * 128, pack_bf16(bf_lo(qw) * w0 * 0.0625f, bf_hi(qw) * w1 * 0.0625f));
          }
          w0 = o0; w1 = o1;
#pragma unroll 1
          for (int i = 31; i >= 0; i--) {
            const int t = tb + i;
            const uint32_t gw = gg[gbase + (size_t)t * 128], kw = gk[gbase + (size_t)t * 128];
            if ((t & bm) == bm) { w0 = 1.f; w1 = 1.f; }
            sts32((la ^ ((t & 7) << 4)) + t * 128 + 2 * TILE, pack_bf16(bf_lo(kw) * w0, bf_hi(kw) * w1));
            w0 *= sigmoid_f(bf_lo(gw)); w1 *= sigmoid_f(bf_hi(gw));
          }
          if (lev < 6) {
            fence_proxy_async();
            bar_sync128<1>();
            float acc[32];
            gemm_qk(acc, desc_k(qkg));
            wg_wait<0>();
            reg_fence(acc);
            const uint32_t tbase = qkg + 5 * TILE + (pw * 16 + (lane & 15)) * 128;
#pragma unroll
            for (int j = 0; j < 8; j += 2)
              stmatrix_x4(tbase + (((j + (lane >> 4)) ^ (lane & 7)) << 4), pack_bf16(acc[4 * j], acc[4 * j + 1]),
                          pack_bf16(acc[4 * j + 2], acc[4 * j + 3]), pack_bf16(acc[4 * j + 4], acc[4 * j + 5]),
                          pack_bf16(acc[4 * j + 6], acc[4 * j + 7]));
            __syncwarp();
#pragma unroll 1
            for (int i = 0; i < 32; i++) {
              const int t = pw * 16 + (i >> 1), sc = (i & 1) * 32 + lane;
              const uint32_t off = t * 128 + (((sc >> 3) ^ (t & 7)) << 4) + (sc & 7) * 2;
              const bool mine = lev < 0 ? (sc >= t) : (sc < t && ((t ^ sc) >> lev) == 1);
              const uint16_t val = sc > t ? (uint16_t)0 : lds16(qkg + 5 * TILE + off);
              if (mine) sts16(qkg + 4 * TILE + off, val);
            }
            bar_sync128<1>();
          }
        }
        if (half) {
          f0 = 1.f; f1 = 1.f;
          sts_f2(carry_cur, 1.f, 1.f);
        } else {
          const float2 cprev = lds_f2(carry_prev);
          const uint32_t wa = enc_decay(cprev.x, cprev.y, res0, res1), wb = enc_decay(w0, w1, res0, res1);
          sts32(qkg + E_OFF + woff, wa);
          sts32(qkg + E_OFF + woff + 256, wb);
          dt0 *= cprev.x; dt1 *= cprev.y;
          sts32(qkg + E_OFF + 768 + cp * 4, pack_bf16(dt0, dt1));
          dt0 *= w0; dt1 *= w1;
        }
        fence_proxy_async();
        bar_sync128<1>();
        operands_ready(true);
      }
      __syncwarp();
      if (lane == 0) mbar_arrive(sb + BAR_AOK + sq * 8);
      __syncwarp();
      TRACE(2, n, 4);
      if (++sq == NQ) { sq = 0; pq ^= 1; }
    }
    bar_sync128<1>();
    if (pw == 0) {
      if (seg < 3 && elect_one()) {
        unsigned int* done = &g_done[((head * 4 + seg + 1) * 2 + rank) * 2];
        uint32_t pe = 0, have = 0;
        int k3 = 0;
#pragma unroll 1
        for (int c = c_end; c < c_next; c++) {
          const uint32_t qkg = sb + OFF_QKG + sq * QKG_BYTES, bar = sb + BAR_RAW + sq * 8;
          if ((uint32_t)(c - c_end) >= have) {
            have = ctr_wait(done, c - c_end);
            asm volatile("fence.proxy.async.global;" ::: "memory");
            TRACE_ANY(2, 14, (c - c_end) >> 1);
          }
#pragma unroll 1
          for (int n = 0; n < 100000 && have < SEGC && !mbar_test(sb + BAR_EMPTY + sq * 8, pe); n++) {
            asm volatile("ld.acquire.gpu.global.u32 %0, [%1];\nfence.proxy.async.global;" : "=r"(have) : "l"(done) : "memory");
          }
          mbar_wait(sb + BAR_EMPTY + sq * 8, pe);
          if (c - c_end < 5) TRACE_ANY(2, 13, c - c_end);
          mbar_expect_tx(bar, 4 * TILE);
          bulk_load_pair(qkg + rank * 2 * TILE, &g_qt[(size_t)(slot0 + 2 * c) * 1024], 2 * TILE, bar);
          if (++sq == NQ) sq = 0;
          if (++k3 == NQ) { k3 = 0; pe ^= 1; }
        }
        asm volatile("st.relaxed.gpu.global.u32 [%0], 0;" ::"l"(done) : "memory");
      }
    } else if (pw == 1) {
      if (elect_one()) {
        unsigned int* done = &g_done[((head * 4 + seg) * 2 + rank) * 2];
        const uint32_t nm = c_end - c_begin;
        mbar_wait(sb + BAR_PUB, 0);
        TRACE_ANY(2, 11, 0);
        if (seg > 0) asm volatile("st.release.gpu.global.u32 [%0], %1;" ::"l"(done), "r"(nm - 2) : "memory");
        TRACE_ANY(2, 11, 1);
        mbar_wait(sb + BAR_PUB + 8, 0);
        const uint32_t vt = sb + OFF_V + ((nm - 1) & 1) * V_BYTES + rank * TILE;
        tma_store(&maps.o, row0 + (c_end - 1) * C, rank, vt);
        tma_store(&maps.o, row0 + (c_end - 1) * C, 2 + rank, vt + 2 * TILE);
        bulk_commit();
        bulk_wait0();
        TRACE_ANY(2, 11, 2);
        if (seg > 0) asm volatile("st.release.gpu.global.u32 [%0], %1;" ::"l"(done), "r"(nm) : "memory");
        TRACE_ANY(2, 11, 3);
      }
    } else if (pw == 2) {
      if (seg == 2) {
        mbar_wait(sb + BAR_XOUT, 0);
        if (lane < 16) tag_wait(&g_hint[head * 64 + 32 + lane * 2], lds32(sb + OFF_CNT + 12));
        __syncwarp();
        if (lane == 0) mbar_arrive(sb + BAR_XIN1);
      }
      if (seg == 1) {
        __stcg(&g_td[(head * 2 + rank) * 32 + lane], lds_f4(sb + OFF_AUXD + lane * 16));
        asm volatile("fence.acq_rel.gpu;" ::: "memory");
        __syncwarp();
        if (lane < 2) asm volatile("red.relaxed.gpu.global.add.u32 [%0], 1;" ::"l"(&g_flag[head * 2 + lane]) : "memory");
        if (lane == 0) TRACE_ANY(2, 12, 1);
      }
    } else {
      const uint32_t tag = (__ldcg(&g_epoch[head]) + 1) & 1;
      if (lane == 0) {
        sts32(sb + OFF_CNT + 12, tag);
        mbar_arrive(sb + BAR_XOUT);
      }
      if (seg == 2) {
        if (lane == 0) flag_wait(&g_flag[head * 2 + rank], 2);
        __syncwarp();
#pragma unroll
        for (int r = 0; r < 2; r++) {
          const float4 d = __ldcg(&g_td[(head * 2 + (rank ^ r)) * 32 + lane]);
          sts_u4(sb + OFF_TD + r * 512 + lane * 16, __float_as_uint(d.x), __float_as_uint(d.y), __float_as_uint(d.z), __float_as_uint(d.w));
        }
      }
      if (seg == 1 || seg == 2) {
        if (lane < 16) tag_wait(&g_hint[head * 64 + lane * 2], tag);
        __syncwarp();
        if (lane == 0) mbar_arrive(sb + BAR_XIN);
      }
    }
  } else {
    asm volatile("setmaxnreg.inc.sync.aligned.u32 216;");
    const int w4 = warp & 3;
    const int mbS = 2 * wg + (1 - rank), mbK = 2 * wg + rank;
    const uint32_t slot = sb + OFF_RECV + wg * TILE + (tid & 127) * 16;
    const uint32_t sma = (((lane >> 4) << 3) + (lane & 7)) * 128 + (((2 * w4 + ((lane >> 3) & 1)) ^ (lane & 7)) << 4);
    const uint32_t peer_delta = mapa(sb, rank ^ 1) - sb;
    constexpr int nmain = SEGC;
    int sq = 0;
    uint32_t pq = 0;
    uint32_t P0[32], P1[32];
    {
      float S0[64], S1[64], O[32];
      uint32_t Ah[8], Af[16];
#pragma unroll
      for (int i = 0; i < 64; i++) { S0[i] = 0.f; S1[i] = 0.f; }
      asm volatile("barrier.cluster.wait.aligned;" ::: "memory");

      mbar_wait(sb + BAR_READY, 0);
      bool slow = __any_sync(0xffffffffu, lds32(sb + OFF_QKG + E_OFF + 512) != 0);
#pragma unroll 1
      for (int m = 0; m < nmain; m++) {
        const int sv = m & 1;
        const uint32_t qkg = sb + OFF_QKG + sq * QKG_BYTES;
        const uint32_t dq = desc_k(qkg);
        const uint32_t dvS = desc_mn(sb + OFF_V + sv * V_BYTES + mbS * TILE);
        const uint32_t dvK = desc_mn(sb + OFF_V + sv * V_BYTES + mbK * TILE);
        const uint32_t e2a = qkg + E_OFF + 256 + (lane & 3) * 16;
        TRACE(wg, m, 0);
        wg_wait<0>();
        cvt_state(Ah, Af, S0);
        reg_fence(Ah);
        reg_fence(Af);
        gemm_inter<true>(O, Ah, Af, S0, dq, slow, e2a, sb + BAR_VT + mbS * 16 + sv * 8, (m >> 1) & 1, sb + BAR_AOK + sq * 8, pq);
        gemm_intra(O, dq, dvS);
        wg_commit();
        gemm_state(S0, dq, dvS);
        wg_commit();
        TRACE(wg, m, 1);
        if (w4 == 0 && m > 0) {
          if (elect_one()) {
            bulk_wait_read0();
            if (m + 1 < nmain) load_v(sb, maps, sv ^ 1, ((cta_id() >> 1) * SEGC + m + 1) * C, mbK);
            else mbar_arrive_remote(sb + BAR_XOK + wg * 8 + peer_delta);
          }
          __syncwarp();
        }
        if (m > 0) mbar_wait(sb + BAR_SENDOK + wg * 8, (m - 1) & 1);
        TRACE(wg, m, 2);
        wg_wait<1>();
        reg_fence(O);
        reg_fence(Af);
        reg_fence(Ah);
#pragma unroll
        for (int i = 0; i < 4; i++)
          st_async_v4(slot + i * 2048 + peer_delta, pack_bf16(O[8 * i], O[8 * i + 1]), pack_bf16(O[8 * i + 2], O[8 * i + 3]),
                      pack_bf16(O[8 * i + 4], O[8 * i + 5]), pack_bf16(O[8 * i + 6], O[8 * i + 7]),
                      sb + BAR_RECV + wg * 8 + peer_delta);
        cvt_state(Ah, Af, S1);
        reg_fence(O);
        reg_fence(Ah);
        reg_fence(Af);
        TRACE(wg, m, 3);
        gemm_inter<false>(O, Ah, Af, S1, dq, slow, e2a, sb + BAR_VT + mbK * 16 + sv * 8, (m >> 1) & 1, 0, 0);
        gemm_intra(O, dq, dvK);
        wg_commit();
        gemm_state(S1, dq, dvK);
        wg_commit();
        reg_fence(S0);
        TRACE(wg, m, 4);
        if (m == nmain - 1) {
          scale_one(S0, sb + OFF_AUXC + (lane & 3) * 16);
          const uint32_t bid = cta_id();
          if (!(bid & 4)) {
            uint32_t tx;
            asm volatile("mov.u32 %0, %%tid.x;" : "=r"(tx));
            mbar_wait(sb + BAR_XOUT, 0);
            const uint32_t tag = lds32(sb + OFF_CNT + 12);
            uint4* dst = &g_state[((bid >> 3) * 4 + (bid & 3)) * 4096 + 2048 + tx];
#pragma unroll
            for (int i = 0; i < 8; i++)
              st_tagged(dst + i * 256, pack_bf16(S0[8 * i], S0[8 * i + 1]), pack_bf16(S0[8 * i + 2], S0[8 * i + 3]),
                        pack_bf16(S0[8 * i + 4], S0[8 * i + 5]), pack_bf16(S0[8 * i + 6], S0[8 * i + 7]), tag);
          }
        }
        const int sq_prev = sq;
        if (++sq == NQ) { sq = 0; pq ^= 1; }
        const bool more = m + 1 < nmain;
        const uint32_t en = more ? sb + OFF_QKG + sq * QKG_BYTES + E_OFF : sb + OFF_AUXC;
        const bool early = __all_sync(0xffffffffu, mbar_test(sb + BAR_READY + sq * 8, pq) || !more);
        mbar_wait(sb + BAR_RECV + wg * 8, m & 1);
        TRACE(wg, m, 5);
        wg_wait<1>();
        reg_fence(O);
        reg_fence(Af);
        reg_fence(Ah);
        uint32_t fl = 0;
        auto load_e = [&]() {
          fl = lds32(en + 512);
#pragma unroll
          for (int i = 0; i < 4; i++) {
            const uint4 e = lds_u4(en + (lane & 3) * 16 + i * 64);
            Af[4 * i] = e.x; Af[4 * i + 1] = e.y; Af[4 * i + 2] = e.z; Af[4 * i + 3] = e.w;
          }
        };
        uint32_t ow[16];
#pragma unroll
        for (int h = 0; h < 2; h++) {
          uint4 pv[2];
          pv[0] = lds_u4(slot + h * 4096);
          pv[1] = lds_u4(slot + h * 4096 + 2048);
          if (h == 0 && early) load_e();
#pragma unroll
          for (int i = 0; i < 2; i++) {
            const float* o = &O[16 * h + 8 * i];
            uint32_t* w = &ow[8 * h + 4 * i];
            w[0] = pack_bf16(o[0] + bf_lo(pv[i].x), o[1] + bf_hi(pv[i].x));
            w[1] = pack_bf16(o[2] + bf_lo(pv[i].y), o[3] + bf_hi(pv[i].y));
            w[2] = pack_bf16(o[4] + bf_lo(pv[i].z), o[5] + bf_hi(pv[i].z));
            w[3] = pack_bf16(o[6] + bf_lo(pv[i].w), o[7] + bf_hi(pv[i].w));
          }
        }
        reg_fence(ow);
        __syncwarp();
        if (elect_one()) mbar_arrive_remote(sb + BAR_SENDOK + wg * 8 + peer_delta);
        uint32_t tx;
        asm volatile("mov.u32 %0, %%tid.x;" : "=r"(tx));
        const uint32_t off = (tx >> 7) * TILE + (tx & 127) * 16;
        const uint4 e = lds_u4(qkg + E_OFF + 768 + (tx >> 7) * 128 + (((tx ^ (tx >> 3)) & 7) << 4));
        uint4 v[4];
        const uint32_t bid = cta_id();
#pragma unroll
        for (int i = 0; i < 4; i++) v[i] = make_uint4(0, 0, 0, 0);
        if (bid & 6) {
#pragma unroll
          for (int i = 0; i < 4; i++) v[i] = lds_u4(qkg + off + i * 2048);
        }
        if (early && more) scale_regs(S0, Af);
        TRACE(wg, m, 6);
        wg_wait<0>();
        reg_fence(S1);
        const uint32_t ot = sb + OFF_V + sv * V_BYTES + mbK * TILE + sma;
#pragma unroll
        for (int i = 0; i < 4; i++) stmatrix_x4_trans(ot + i * 2048, ow[4 * i], ow[4 * i + 1], ow[4 * i + 2], ow[4 * i + 3]);
        fence_proxy_async();
        if (bid & 6) {
          uint4* dst = &g_qt[(size_t)(((bid >> 1) * SEGC + m) * 2 + (bid & 1)) * 1024 + (off >> 4)];
#pragma unroll
          for (int i = 0; i < 4; i++)
            __stcg(dst + i * 128, make_uint4(mul_bf16x2(v[i].x, e.x), mul_bf16x2(v[i].y, e.y),
                                             mul_bf16x2(v[i].z, e.z), mul_bf16x2(v[i].w, e.w)));
        }
        if (wg == 0) bar_sync128<2>(); else bar_sync128<3>();
        TRACE(wg, m, 7);
        if (elect_one()) {
          const int row = ((cta_id() >> 1) * SEGC + m) * C;
          if (w4 == 0) {
            if (m >= nmain - 2) { bulk_wait0(); mbar_arrive(sb + BAR_PUB + (more ? 0 : 8)); }
            if (more) {
              tma_store(&maps.o, row, mbK, sb + OFF_V + sv * V_BYTES + mbK * TILE);
              bulk_commit();
            }
          } else if (w4 == 1) {
            if (m + 3 < nmain) {
              uint32_t old;
              asm volatile("atom.relaxed.cta.shared::cta.inc.u32 %0, [%1], 1;" : "=r"(old) : "r"(sb + OFF_CNT + sq_prev * 4) : "memory");
              if (old == 1) load_qkg(sb, maps, sq_prev, row + 3 * C, rank);
            } else {
              mbar_arrive(sb + BAR_EMPTY + sq_prev * 8);
              mbar_arrive_remote(sb + BAR_EMPTY + sq_prev * 8 + peer_delta);
            }
          } else if (w4 == 2) {
            if (more) mbar_expect_tx(sb + BAR_RECV + wg * 8, TILE);
          } else if (m + 2 < nmain) {
            load_v(sb, maps, sv, row + 2 * C, mbS);
          }
        }
        __syncwarp();
        if (!early) {
          mbar_wait(sb + BAR_READY + sq * 8, pq);
          load_e();
          scale_regs(S0, Af);
        }
        slow = __any_sync(0xffffffffu, fl != 0);
        scale_regs(S1, Af);
      }
      TRACE(wg, 39, 1);
#pragma unroll
      for (int i = 0; i < 32; i++) {
        P1[i] = pack_bf16(S0[2 * i], S0[2 * i + 1]);
        P0[i] = pack_bf16(S1[2 * i], S1[2 * i + 1]);
      }
    }
    const int seg = (cta_id() >> 1) & 3;
    if (seg < 3) {
      const uint32_t xrecv = sb + OFF_V + (nmain & 1) * V_BYTES + wg * 2 * TILE + (tid & 127) * 16;
      const uint32_t xa = (lane & 3) * 16;
      uint32_t bx, tx;
      asm volatile("mov.u32 %0, %%ctaid.x;" : "=r"(bx));
      asm volatile("mov.u32 %0, %%tid.x;" : "=r"(tx));
      uint4* gs = &g_state[(size_t)(bx >> 3) * (4 * 4096) + tx];
      TRACE(wg, 39, 4);
      mbar_wait(sb + BAR_XOUT, 0);
      const uint32_t tag = lds32(sb + OFF_CNT + 12);
      uint4* hint = &g_hint[(bx >> 3) * 64 + (tx >> 5) * 2];
      if (seg < 2) {
        uint4* dst = gs + (bx & 3) * 4096;
#pragma unroll
        for (int i = 0; i < 8; i++) {
          st_tagged(dst + i * 256, P0[4 * i], P0[4 * i + 1], P0[4 * i + 2], P0[4 * i + 3], tag);
        }
        if (lane == 0)
          asm volatile("st.relaxed.gpu.global.u32 [%0], %1;" ::"l"(hint + (bx & 3) * 16), "r"(tag) : "memory");
      }
      mbar_wait(sb + BAR_XOK + wg * 8, 0);
#pragma unroll
      for (int i = 0; i < 8; i++)
        st_async_v4(xrecv + i * 2048 + peer_delta, P1[4 * i], P1[4 * i + 1], P1[4 * i + 2], P1[4 * i + 3],
                    sb + BAR_XRECV + wg * 8 + peer_delta);
      if (w4 == 0) {
        const float4 td = lds_f4(sb + OFF_AUXD + lane * 16);
        st_async_v4(sb + OFF_CARRY + wg * 512 + lane * 16 + peer_delta, __float_as_uint(td.x), __float_as_uint(td.y),
                    __float_as_uint(td.z), __float_as_uint(td.w), sb + BAR_XRECV + wg * 8 + peer_delta);
      }
      TRACE(wg, 39, 5);
      auto take_peer = [&]() {
        mbar_wait(sb + BAR_XRECV + wg * 8, 0);
        TRACE(wg, 39, 6);
#pragma unroll
        for (int i = 0; i < 8; i++) {
          const uint4 v = lds_u4(xrecv + i * 2048);
          P1[4 * i] = v.x; P1[4 * i + 1] = v.y; P1[4 * i + 2] = v.z; P1[4 * i + 3] = v.w;
        }
      };
      if (seg == 0) take_peer();
      if (seg > 0) {
        const uint32_t rk = bx & 1;
        const uint4* own = gs + rk * 4096;
        const uint4* oth = gs + (rk ^ 1) * 4096 + 2048;
        auto fetch = [&](uint4 (&x)[16], int src) {
#pragma unroll
          for (int i = 0; i < 8; i++) { x[i] = ld_tagged(own + src * 8192 + i * 256); x[8 + i] = ld_tagged(oth + src * 8192 + i * 256); }
        };
        auto check = [&](uint4 (&x)[16], int src) {
#pragma unroll 1
          for (int n = 0; n < 100000; n++) {
            uint32_t all = 1, any = 0;
#pragma unroll
            for (int i = 0; i < 16; i++) { all &= x[i].x & x[i].z; any |= x[i].x | x[i].z; }
            if ((tag ? all : ~any) & 1) break;
            fetch(x, src);
          }
          __syncwarp();
        };
        uint4 x[16];
        mbar_wait(sb + BAR_XIN, 0);
        TRACE(wg, 39, 7);
        if (seg == 2) {
          uint4 y[16];
          fetch(y, 0);
          mbar_wait(sb + BAR_XIN1, 0);
          fetch(x, 1);
          check(y, 0);
          check(x, 1);
#pragma unroll
          for (int i = 0; i < 16; i++) axpy_frag(&x[i].x, lds_f4(sb + OFF_TD + xa + i * 64), y[i]);
        } else {
          fetch(x, 0);
          check(x, 0);
        }
        take_peer();
#pragma unroll
        for (int i = 0; i < 8; i++) {
          axpy_frag(&P0[4 * i], lds_f4(sb + OFF_AUXD + xa + i * 64), x[i]);
          axpy_frag(&P1[4 * i], lds_f4(sb + OFF_CARRY + wg * 512 + xa + i * 64), x[8 + i]);
        }
      }
      TRACE(wg, 39, 2);
      constexpr int ncorr = SEGC;
      const uint32_t tileA = sb + OFF_RECV + wg * TILE;
      const uint32_t tileB = sb + OFF_QKG + ((sq + wg) % NQ) * QKG_BYTES + 4 * TILE;
      if (wg == 1) asm volatile("bar.arrive 7, 256;" ::: "memory");
      float Oa[32], Ob[32];
      auto issue = [&](float (&O)[32], int k) {
        const uint32_t dq = desc_k(sb + OFF_QKG + sq * QKG_BYTES);
        mbar_wait(sb + BAR_RAW + sq * 8, pq);
        TRACE(wg, nmain + k, 0);
        asm volatile("bar.sync %0, 256;" ::"r"(7 + wg) : "memory");
        gemm_corr<0>(O, P0, dq + rank * ((2 * TILE) >> 4));
        gemm_corr<1>(O, P1, dq + (rank ^ 1) * ((2 * TILE) >> 4));
        if (wg == 0 || k + 1 < ncorr) asm volatile("bar.arrive %0, 256;" ::"r"(8 - wg) : "memory");
        TRACE(wg, nmain + k, 1);
        if (++sq == NQ) { sq = 0; pq ^= 1; }
      };
      auto finish = [&](float (&O)[32], int k, uint32_t tile) {
        reg_fence(O);
        TRACE(wg, nmain + k, 2);
        store_o(O, tile + sma);
        fence_proxy_async();
        if (w4 == 0) {
          if (elect_one()) bulk_wait_read0();
        }
        wg_wait<0>();
        if (wg == 0) bar_sync128<2>(); else bar_sync128<3>();
        if (w4 == 0) {
          if (elect_one()) {
            tma_reduce_add(&maps.o, ((cta_id() >> 1) * SEGC + SEGC + k) * C, mbK, tile);
            bulk_commit();
          }
        }
        if (w4 == 1 && k + 1 + NQ < ncorr) {
          if (elect_one()) {
            const uint32_t eb = sb + BAR_EMPTY + ((SEGC + k + 1) % NQ) * 8;
            mbar_arrive(eb);
            mbar_arrive_remote(eb + peer_delta);
          }
        }
        __syncwarp();
        TRACE(wg, nmain + k, 3);
      };
      issue(Oa, 0);
      wg_wait<0>();
      if (wg == 0) bar_sync128<2>(); else bar_sync128<3>();
      if (w4 == 1) {
        if (elect_one()) {
          mbar_arrive(sb + BAR_EMPTY + (SEGC % NQ) * 8);
          mbar_arrive_remote(sb + BAR_EMPTY + (SEGC % NQ) * 8 + peer_delta);
        }
        __syncwarp();
      }
#pragma unroll 1
      for (int k = 0; k < ncorr; k += 2) {
        issue(Ob, k + 1);
        wg_wait<2>();
        finish(Oa, k, tileA);
        if (k + 2 < ncorr) { issue(Oa, k + 2); wg_wait<2>(); }
        finish(Ob, k + 1, tileB);
      }
    }
    if (w4 == 0) {
      if (elect_one()) bulk_wait0();
    }
    TRACE(wg, 39, 3);
    TRACE_DUMP(wg);
    if (wg == 0) TRACE_DUMP(2);
    asm volatile("barrier.cluster.arrive.relaxed.aligned;\nbarrier.cluster.wait.aligned;" ::: "memory");
    if ((blockIdx.x & 7) == 4 && threadIdx.x == 0) atomicAdd(&g_epoch[blockIdx.x >> 3], 1u);
  }
}

typedef CUresult (*EncodeFn)(CUtensorMap*, CUtensorMapDataType, cuuint32_t, void*, const cuuint64_t*, const cuuint64_t*,
                             const cuuint32_t*, const cuuint32_t*, CUtensorMapInterleave, CUtensorMapSwizzle,
                             CUtensorMapL2promotion, CUtensorMapFloatOOBfill);

static void make_map(EncodeFn fn, CUtensorMap* m, const void* ptr, int nblk) {
  cuuint64_t dims[3] = {64, (cuuint64_t)H * T, 4};
  cuuint64_t strides[2] = {(cuuint64_t)D * 2, 128};
  cuuint32_t box[3] = {64, 64, (cuuint32_t)nblk};
  cuuint32_t es[3] = {1, 1, 1};
  fn(m, CU_TENSOR_MAP_DATA_TYPE_BFLOAT16, 3, const_cast<void*>(ptr), dims, strides, box, es, CU_TENSOR_MAP_INTERLEAVE_NONE,
     CU_TENSOR_MAP_SWIZZLE_128B, CU_TENSOR_MAP_L2_PROMOTION_L2_128B, CU_TENSOR_MAP_FLOAT_OOB_FILL_NONE);
}

}

extern "C" void kernel_launch(void* const* d_in, const int* in_sizes, int n_in, void* d_out, int out_size) {
  using namespace gla;
  static EncodeFn fn = nullptr;
  if (!fn) {
    void* p = nullptr;
    cudaDriverEntryPointQueryResult qr;
    cudaGetDriverEntryPoint("cuTensorMapEncodeTiled", &p, cudaEnableDefault, &qr);
    fn = (EncodeFn)p;
    cudaFuncSetAttribute(gla_kernel, cudaFuncAttributeMaxDynamicSharedMemorySize, SMEM_TOTAL);
  }
  Maps maps;
  make_map(fn, &maps.q, d_in[0], 2);
  make_map(fn, &maps.k, d_in[1], 2);
  make_map(fn, &maps.v, d_in[2], 1);
  make_map(fn, &maps.g, d_in[3], 2);
  make_map(fn, &maps.o, d_out, 1);
  gla_kernel<<<H * 4 * 2, 384, SMEM_TOTAL, cudaStreamPerThread>>>(maps, (const uint32_t*)d_in[0], (const uint32_t*)d_in[1],
                                                                 (const uint32_t*)d_in[3]);
}
```
